```python
import torch

def _softmax(x, axis=-1):
    return torch.softmax(x, dim=axis)

def _gelu(x):
    return torch.nn.functional.gelu(x, approximate='tanh')

def _silu(x):
    return torch.nn.functional.silu(x)

def _sigmoid(x):
    return torch.sigmoid(x)

def _layernorm(x, axis=-1, eps=1e-05):
    m = x.mean(dim=axis, keepdim=True)
    v = x.var(dim=axis, keepdim=True, unbiased=False)
    return (x - m) / torch.sqrt(v + eps)

def _scatter_add(tgt, idx, src, axis=0):
    return tgt.clone().index_add_(axis, idx, src)

def _segment_sum(src, seg, n):
    out = torch.zeros((n,) + src.shape[1:], dtype=src.dtype)
    return out.index_add_(0, seg, src)

def _pad(x, pw):
    flat = tuple((v for pair in reversed(pw) for v in pair))
    return torch.nn.functional.pad(x, flat)
kernel_name = 'adaLN_cond__mha_block__glu_gated_bilinear__prompt'

def setup_inputs():

    _w = lambda a: (lambda t: t.to(torch.bfloat16) if t.is_floating_point() else t)(torch.as_tensor(a))

    def _A_setup():
        B, S, D, H = (1, 2048, 640, 32)
        return {'x': _w((lambda *s: torch.randn(*s, dtype=torch.bfloat16) * 0.05)(B, S, D)), 'wqkv': _w((lambda *s: torch.randn(*s, dtype=torch.bfloat16) * 0.05)(D, 3 * D)), 'wo': _w((lambda *s: torch.randn(*s, dtype=torch.bfloat16) * 0.05)(D, D))}
    _A_in = _A_setup()

    def _B_setup():
        B, S, D, F = (1, 2048, 640, 1536)
        return {'x': _w((lambda *s: torch.randn(*s, dtype=torch.bfloat16) * 0.05)(B, S, D)), 'w_gate': _w((lambda *s: torch.randn(*s, dtype=torch.bfloat16) * 0.8)(D, F) * D ** (-0.5)), 'w_up': _w((lambda *s: torch.randn(*s, dtype=torch.bfloat16) * 0.8)(D, F) * D ** (-0.5)), 'w_down': _w((lambda *s: torch.randn(*s, dtype=torch.bfloat16) * 0.8)(F, D) * F ** (-0.5))}
    _B_in = _B_setup()
    return {'A_x': _A_in['x'], 'A_wqkv': _A_in['wqkv'], 'A_wo': _A_in['wo'], 'B_x': _B_in['x'], 'B_w_gate': _B_in['w_gate'], 'B_w_up': _B_in['w_up'], 'B_w_down': _B_in['w_down'], 'c': _w((lambda *s: torch.randn(*s, dtype=torch.bfloat16) * 0.1)(1, 640) * 8.0), 'w_mod': _w((lambda *s: torch.randn(*s, dtype=torch.bfloat16) * 0.1)(640, 6 * 640) * 640 ** (-0.5) * 8.0)}

def reference(A_x, A_wqkv, A_wo, B_x, B_w_gate, B_w_up, B_w_down, c, w_mod):

    def _A_ref(x, wqkv, wo):
        B, S, D = x.shape
        H = 32
        Dh = D // H
        qkv = (lambda x, *d: x.permute(*d))((x @ wqkv).reshape(B, S, 3, H, Dh), 2, 0, 3, 1, 4)
        q, k, v = (qkv[0], qkv[1], qkv[2])
        scores = torch.einsum('bhqd,bhkd->bhqk', q, k) * Dh ** (-0.5)
        p = _softmax(scores, axis=-1)
        o = torch.einsum('bhqk,bhkd->bhqd', p, v)
        return (lambda x, *d: x.permute(*d))(o, 0, 2, 1, 3).reshape(B, S, D) @ wo

    def _B_ref(x, w_gate, w_up, w_down):
        g = torch.einsum('bsd,df->bsf', x, w_gate)
        u = torch.einsum('bsd,df->bsf', x, w_up)
        h = g * u
        return torch.einsum('bsf,fd->bsd', h, w_down)
    x = A_x
    mod = (_silu(c) @ w_mod).reshape(c.shape[0], 6, 1, -1)
    sa, ca, ga, sb, cb, gb = (mod[:, 0].clone(), mod[:, 1].clone(), mod[:, 2].clone(), mod[:, 3].clone(), mod[:, 4].clone(), mod[:, 5].clone())
    h = _layernorm(x, axis=-1) * (1 + ca) + sa
    x = x + ga * _A_ref(h, A_wqkv, A_wo)
    h = _layernorm(x, axis=-1) * (1 + cb) + sb
    x = x + gb * _B_ref(h, B_w_gate, B_w_up, B_w_down)
    return x
```

```cpp
#include <cuda_runtime.h>
#include <cuda_bf16.h>
#include <cuda.h>
#include <stdint.h>

typedef __nv_bfloat16 bf16;

constexpr int S_LEN = 2048, DM = 640, NH = 32, FF = 1536;
constexpr int PIECE_B = 3 * 128 * 16;
#define POLYMASK 0xDADA

__device__ __align__(1024) bf16 g_mod[6 * DM];
__device__ __align__(1024) unsigned char g_kv[NH * 16 * 2 * PIECE_B];
__device__ __align__(1024) float g_nrm[8 * 16 * 8];
__device__ __align__(1024) unsigned char g_o[32 * NH * 3072];
__device__ __align__(1024) bf16 g_x1[S_LEN * DM];
__device__ __align__(1024) bf16 g_hh[S_LEN * FF];
__device__ __align__(1024) unsigned char g_wp[8 * 10 * 49152];
__device__ __align__(1024) unsigned char g_wpk[4 * 36 * 20480];
__device__ __align__(1024) float g_s12[8 * 4 * 192];
__device__ __align__(1024) uint2 g_st1[S_LEN];
__device__ __align__(1024) uint32_t g_modt[2 * DM];
__device__ __align__(1024) float2 g_st2[S_LEN * 4];
__device__ __align__(1024) uint32_t g_sync[224 * 32];

__device__ __forceinline__ uint32_t smem_u32(const void* p) { return (uint32_t)__cvta_generic_to_shared(p); }
__device__ __forceinline__ void mbar_init(uint32_t bar, int cnt) { asm volatile("mbarrier.init.shared::cta.b64 [%0], %1;" ::"r"(bar), "r"(cnt) : "memory"); }
__device__ __forceinline__ void mbar_expect(uint32_t bar, uint32_t bytes) { asm volatile("mbarrier.arrive.expect_tx.shared::cta.b64 _, [%0], %1;" ::"r"(bar), "r"(bytes) : "memory"); }
__device__ __forceinline__ void mbar_arrive(uint32_t bar) { asm volatile("mbarrier.arrive.shared::cta.b64 _, [%0];" ::"r"(bar) : "memory"); }
__device__ __forceinline__ void mbar_arrive_cluster(uint32_t bar, uint32_t cta) {
  asm volatile("{\n.reg .b32 ra;\nmapa.shared::cluster.u32 ra, %0, %1;\nmbarrier.arrive.shared::cluster.b64 _, [ra];\n}" ::"r"(bar), "r"(cta) : "memory");
}
__device__ __forceinline__ bool mbar_try(uint32_t bar, uint32_t parity) {
  uint32_t ok;
  asm volatile("{\n.reg .pred p;\nmbarrier.try_wait.parity.shared::cta.b64 p, [%1], %2;\nselp.u32 %0, 1, 0, p;\n}" : "=r"(ok) : "r"(bar), "r"(parity) : "memory");
  return ok;
}
template <bool TRAP = false>
__device__ __forceinline__ void mbar_wait(uint32_t bar, uint32_t parity) {
  if (mbar_try(bar, parity)) return;
  uint32_t n = 0;
#pragma unroll 1
  while (!mbar_try(bar, parity)) {
    if (++n > (1u << 20)) {
      if (TRAP) __trap(); else break;
    }
  }
}
__device__ __forceinline__ void fence_mbar_init() { asm volatile("fence.mbarrier_init.release.cluster;" ::: "memory"); }
__device__ __forceinline__ void fence_async_smem() { asm volatile("fence.proxy.async.shared::cta;" ::: "memory"); }
__device__ __forceinline__ void named_bar(int id, int n) { asm volatile("bar.sync %0, %1;" ::"r"(id), "r"(n) : "memory"); }

__device__ __forceinline__ void bulk_g2s(uint32_t dst, const void* src, uint32_t bytes, uint32_t bar) {
  asm volatile("cp.async.bulk.shared::cluster.global.mbarrier::complete_tx::bytes [%0], [%1], %2, [%3];" ::"r"(dst), "l"(src), "r"(bytes), "r"(bar) : "memory");
}
__device__ __forceinline__ void bulk_s2g(void* dst, uint32_t src, uint32_t bytes) {
  asm volatile("cp.async.bulk.global.shared::cta.bulk_group [%0], [%1], %2;" ::"l"(dst), "r"(src), "r"(bytes) : "memory");
}
__device__ __forceinline__ void bulk_commit() { asm volatile("cp.async.bulk.commit_group;" ::: "memory"); }
__device__ __forceinline__ void bulk_wait_read() { asm volatile("cp.async.bulk.wait_group.read 0;" ::: "memory"); }
__device__ __forceinline__ void tmap_prefetch(const CUtensorMap* m) { asm volatile("prefetch.tensormap [%0];" ::"l"(m) : "memory"); }

__device__ __forceinline__ void tma2d(uint32_t dst, const CUtensorMap* m, int c0, int c1, uint32_t bar) {
  asm volatile("cp.async.bulk.tensor.2d.shared::cluster.global.mbarrier::complete_tx::bytes [%0], [%1, {%3, %4}], [%2];" ::"r"(dst), "l"(m), "r"(bar), "r"(c0), "r"(c1) : "memory");
}
__device__ __forceinline__ void tma2d_mc(uint32_t dst, const CUtensorMap* m, int c0, int c1, uint32_t bar, uint16_t mask) {
  asm volatile("cp.async.bulk.tensor.2d.shared::cluster.global.mbarrier::complete_tx::bytes.multicast::cluster [%0], [%1, {%3, %4}], [%2], %5;" ::"r"(dst), "l"(m), "r"(bar), "r"(c0), "r"(c1), "h"(mask) : "memory");
}
__device__ __forceinline__ void tma3d(uint32_t dst, const CUtensorMap* m, int c0, int c1, int c2, uint32_t bar) {
  asm volatile("cp.async.bulk.tensor.3d.shared::cluster.global.mbarrier::complete_tx::bytes [%0], [%1, {%3, %4, %5}], [%2];" ::"r"(dst), "l"(m), "r"(bar), "r"(c0), "r"(c1), "r"(c2) : "memory");
}
__device__ __forceinline__ void tma3d_mc(uint32_t dst, const CUtensorMap* m, int c0, int c1, int c2, uint32_t bar, uint16_t mask) {
  asm volatile("cp.async.bulk.tensor.3d.shared::cluster.global.mbarrier::complete_tx::bytes.multicast::cluster [%0], [%1, {%3, %4, %5}], [%2], %6;" ::"r"(dst), "l"(m), "r"(bar), "r"(c0), "r"(c1), "r"(c2), "h"(mask) : "memory");
}
__device__ __forceinline__ void tma3d_store(const CUtensorMap* m, int c0, int c1, int c2, uint32_t src) {
  asm volatile("cp.async.bulk.tensor.3d.global.shared::cta.bulk_group [%0, {%2, %3, %4}], [%1];" ::"l"(m), "r"(src), "r"(c0), "r"(c1), "r"(c2) : "memory");
}

__device__ __forceinline__ void wg_fence() { asm volatile("wgmma.fence.sync.aligned;" ::: "memory"); }
__device__ __forceinline__ void wg_commit() { asm volatile("wgmma.commit_group.sync.aligned;" ::: "memory"); }
template <int N> __device__ __forceinline__ void wg_wait() { asm volatile("wgmma.wait_group.sync.aligned %0;" ::"n"(N) : "memory"); }
__device__ __forceinline__ uint64_t make_desc(uint32_t addr, uint32_t lbo, uint32_t sbo, uint32_t swz) {
  return (uint64_t)((addr & 0x3FFFF) >> 4) | ((uint64_t)((lbo & 0x3FFFF) >> 4) << 16) | ((uint64_t)(sbo >> 4) << 32) | ((uint64_t)swz << 62);
}
template <int N> __device__ __forceinline__ void reg_fence(float (&d)[N]) {
#pragma unroll
  for (int i = 0; i < N; i++) asm volatile("" : "+f"(d[i])::"memory");
}
template <int N> __device__ __forceinline__ void reg_fence(uint32_t (&d)[N]) {
#pragma unroll
  for (int i = 0; i < N; i++) asm volatile("" : "+r"(d[i])::"memory");
}
__device__ __forceinline__ float ex2(float x) { float y; asm("ex2.approx.ftz.f32 %0, %1;" : "=f"(y) : "f"(x)); return y; }
__device__ __forceinline__ uint32_t pack_bf16(float lo, float hi) { uint32_t r; asm("cvt.rn.bf16x2.f32 %0, %1, %2;" : "=r"(r) : "f"(hi), "f"(lo)); return r; }
__device__ __forceinline__ float bf_lo(uint32_t v) { return __uint_as_float(v << 16); }
__device__ __forceinline__ float bf_hi(uint32_t v) { return __uint_as_float(v & 0xFFFF0000u); }
__device__ __forceinline__ float bf_round(float x) { return __bfloat162float(__float2bfloat16_rn(x)); }
__device__ __forceinline__ uint32_t bf2_mul(uint32_t a, uint32_t b) { uint32_t r; asm("mul.rn.bf16x2 %0, %1, %2;" : "=r"(r) : "r"(a), "r"(b)); return r; }
__device__ __forceinline__ uint32_t bf2_add(uint32_t a, uint32_t b) { uint32_t r; asm("add.rn.bf16x2 %0, %1, %2;" : "=r"(r) : "r"(a), "r"(b)); return r; }
__device__ __forceinline__ uint32_t bf2_sub(uint32_t a, uint32_t b) { uint32_t r; asm("sub.rn.bf16x2 %0, %1, %2;" : "=r"(r) : "r"(a), "r"(b)); return r; }
__device__ __forceinline__ void ldsm4(uint32_t addr, uint32_t& r0, uint32_t& r1, uint32_t& r2, uint32_t& r3) {
  asm volatile("ldmatrix.sync.aligned.m8n8.x4.shared.b16 {%0, %1, %2, %3}, [%4];" : "=r"(r0), "=r"(r1), "=r"(r2), "=r"(r3) : "r"(addr) : "memory");
}
__device__ __forceinline__ void stsm4(uint32_t addr, uint32_t r0, uint32_t r1, uint32_t r2, uint32_t r3) {
  asm volatile("stmatrix.sync.aligned.m8n8.x4.shared.b16 [%0], {%1, %2, %3, %4};" ::"r"(addr), "r"(r0), "r"(r1), "r"(r2), "r"(r3) : "memory");
}
__device__ __forceinline__ void sts32(uint32_t addr, uint32_t v) { asm volatile("st.shared.b32 [%0], %1;" ::"r"(addr), "r"(v) : "memory"); }
__device__ __forceinline__ void sts64(uint32_t addr, uint32_t a, uint32_t b) { asm volatile("st.shared.v2.b32 [%0], {%1, %2};" ::"r"(addr), "r"(a), "r"(b) : "memory"); }

__device__ __forceinline__ void wgmma_rs_n160_tb1(float (&d)[80], uint32_t a0, uint32_t a1, uint32_t a2, uint32_t a3, uint64_t db, int scale_d) {
  asm volatile("{\n.reg .pred p;\nsetp.ne.b32 p, %85, 0;\n"
      "wgmma.mma_async.sync.aligned.m64n160k16.f32.bf16.bf16 {"
      "%0, %1, %2, %3, %4, %5, %6, %7, %8, %9, %10, %11, %12, %13, %14, %15, "
      "%16, %17, %18, %19, %20, %21, %22, %23, %24, %25, %26, %27, %28, %29, %30, %31, "
      "%32, %33, %34, %35, %36, %37, %38, %39, %40, %41, %42, %43, %44, %45, %46, %47, "
      "%48, %49, %50, %51, %52, %53, %54, %55, %56, %57, %58, %59, %60, %61, %62, %63, "
      "%64, %65, %66, %67, %68, %69, %70, %71, %72, %73, %74, %75, %76, %77, %78, %79}, {%80, %81, %82, %83}, %84, p, 1, 1, 1;\n}\n"
    :
      "+f"(d[0]), "+f"(d[1]), "+f"(d[2]), "+f"(d[3]), "+f"(d[4]), "+f"(d[5]), "+f"(d[6]), "+f"(d[7]),
      "+f"(d[8]), "+f"(d[9]), "+f"(d[10]), "+f"(d[11]), "+f"(d[12]), "+f"(d[13]), "+f"(d[14]), "+f"(d[15]),
      "+f"(d[16]), "+f"(d[17]), "+f"(d[18]), "+f"(d[19]), "+f"(d[20]), "+f"(d[21]), "+f"(d[22]), "+f"(d[23]),
      "+f"(d[24]), "+f"(d[25]), "+f"(d[26]), "+f"(d[27]), "+f"(d[28]), "+f"(d[29]), "+f"(d[30]), "+f"(d[31]),
      "+f"(d[32]), "+f"(d[33]), "+f"(d[34]), "+f"(d[35]), "+f"(d[36]), "+f"(d[37]), "+f"(d[38]), "+f"(d[39]),
      "+f"(d[40]), "+f"(d[41]), "+f"(d[42]), "+f"(d[43]), "+f"(d[44]), "+f"(d[45]), "+f"(d[46]), "+f"(d[47]),
      "+f"(d[48]), "+f"(d[49]), "+f"(d[50]), "+f"(d[51]), "+f"(d[52]), "+f"(d[53]), "+f"(d[54]), "+f"(d[55]),
      "+f"(d[56]), "+f"(d[57]), "+f"(d[58]), "+f"(d[59]), "+f"(d[60]), "+f"(d[61]), "+f"(d[62]), "+f"(d[63]),
      "+f"(d[64]), "+f"(d[65]), "+f"(d[66]), "+f"(d[67]), "+f"(d[68]), "+f"(d[69]), "+f"(d[70]), "+f"(d[71]),
      "+f"(d[72]), "+f"(d[73]), "+f"(d[74]), "+f"(d[75]), "+f"(d[76]), "+f"(d[77]), "+f"(d[78]), "+f"(d[79])
    : "r"(a0), "r"(a1), "r"(a2), "r"(a3), "l"(db), "r"(scale_d));
}
__device__ __forceinline__ void wgmma_rs_n40_tb1(float (&d)[20], uint32_t a0, uint32_t a1, uint32_t a2, uint32_t a3, uint64_t db, int scale_d) {
  asm volatile("{\n.reg .pred p;\nsetp.ne.b32 p, %25, 0;\n"
      "wgmma.mma_async.sync.aligned.m64n40k16.f32.bf16.bf16 {"
      "%0, %1, %2, %3, %4, %5, %6, %7, %8, %9, %10, %11, %12, %13, %14, %15, "
      "%16, %17, %18, %19}, {%20, %21, %22, %23}, %24, p, 1, 1, 1;\n}\n"
    :
      "+f"(d[0]), "+f"(d[1]), "+f"(d[2]), "+f"(d[3]), "+f"(d[4]), "+f"(d[5]), "+f"(d[6]), "+f"(d[7]),
      "+f"(d[8]), "+f"(d[9]), "+f"(d[10]), "+f"(d[11]), "+f"(d[12]), "+f"(d[13]), "+f"(d[14]), "+f"(d[15]),
      "+f"(d[16]), "+f"(d[17]), "+f"(d[18]), "+f"(d[19])
    : "r"(a0), "r"(a1), "r"(a2), "r"(a3), "l"(db), "r"(scale_d));
}
__device__ __forceinline__ void wgmma_ss_n192_tb1(float (&d)[96], uint64_t da, uint64_t db, int scale_d) {
  asm volatile("{\n.reg .pred p;\nsetp.ne.b32 p, %98, 0;\n"
      "wgmma.mma_async.sync.aligned.m64n192k16.f32.bf16.bf16 {"
      "%0, %1, %2, %3, %4, %5, %6, %7, %8, %9, %10, %11, %12, %13, %14, %15, "
      "%16, %17, %18, %19, %20, %21, %22, %23, %24, %25, %26, %27, %28, %29, %30, %31, "
      "%32, %33, %34, %35, %36, %37, %38, %39, %40, %41, %42, %43, %44, %45, %46, %47, "
      "%48, %49, %50, %51, %52, %53, %54, %55, %56, %57, %58, %59, %60, %61, %62, %63, "
      "%64, %65, %66, %67, %68, %69, %70, %71, %72, %73, %74, %75, %76, %77, %78, %79, "
      "%80, %81, %82, %83, %84, %85, %86, %87, %88, %89, %90, %91, %92, %93, %94, %95}, %96, %97, p, 1, 1, 0, 1;\n}\n"
    :
      "+f"(d[0]), "+f"(d[1]), "+f"(d[2]), "+f"(d[3]), "+f"(d[4]), "+f"(d[5]), "+f"(d[6]), "+f"(d[7]),
      "+f"(d[8]), "+f"(d[9]), "+f"(d[10]), "+f"(d[11]), "+f"(d[12]), "+f"(d[13]), "+f"(d[14]), "+f"(d[15]),
      "+f"(d[16]), "+f"(d[17]), "+f"(d[18]), "+f"(d[19]), "+f"(d[20]), "+f"(d[21]), "+f"(d[22]), "+f"(d[23]),
      "+f"(d[24]), "+f"(d[25]), "+f"(d[26]), "+f"(d[27]), "+f"(d[28]), "+f"(d[29]), "+f"(d[30]), "+f"(d[31]),
      "+f"(d[32]), "+f"(d[33]), "+f"(d[34]), "+f"(d[35]), "+f"(d[36]), "+f"(d[37]), "+f"(d[38]), "+f"(d[39]),
      "+f"(d[40]), "+f"(d[41]), "+f"(d[42]), "+f"(d[43]), "+f"(d[44]), "+f"(d[45]), "+f"(d[46]), "+f"(d[47]),
      "+f"(d[48]), "+f"(d[49]), "+f"(d[50]), "+f"(d[51]), "+f"(d[52]), "+f"(d[53]), "+f"(d[54]), "+f"(d[55]),
      "+f"(d[56]), "+f"(d[57]), "+f"(d[58]), "+f"(d[59]), "+f"(d[60]), "+f"(d[61]), "+f"(d[62]), "+f"(d[63]),
      "+f"(d[64]), "+f"(d[65]), "+f"(d[66]), "+f"(d[67]), "+f"(d[68]), "+f"(d[69]), "+f"(d[70]), "+f"(d[71]),
      "+f"(d[72]), "+f"(d[73]), "+f"(d[74]), "+f"(d[75]), "+f"(d[76]), "+f"(d[77]), "+f"(d[78]), "+f"(d[79]),
      "+f"(d[80]), "+f"(d[81]), "+f"(d[82]), "+f"(d[83]), "+f"(d[84]), "+f"(d[85]), "+f"(d[86]), "+f"(d[87]),
      "+f"(d[88]), "+f"(d[89]), "+f"(d[90]), "+f"(d[91]), "+f"(d[92]), "+f"(d[93]), "+f"(d[94]), "+f"(d[95])
    : "l"(da), "l"(db), "r"(scale_d));
}
__device__ __forceinline__ void wgmma_ss_n160_tb1(float (&d)[80], uint64_t da, uint64_t db, int scale_d) {
  asm volatile("{\n.reg .pred p;\nsetp.ne.b32 p, %82, 0;\n"
      "wgmma.mma_async.sync.aligned.m64n160k16.f32.bf16.bf16 {"
      "%0, %1, %2, %3, %4, %5, %6, %7, %8, %9, %10, %11, %12, %13, %14, %15, "
      "%16, %17, %18, %19, %20, %21, %22, %23, %24, %25, %26, %27, %28, %29, %30, %31, "
      "%32, %33, %34, %35, %36, %37, %38, %39, %40, %41, %42, %43, %44, %45, %46, %47, "
      "%48, %49, %50, %51, %52, %53, %54, %55, %56, %57, %58, %59, %60, %61, %62, %63, "
      "%64, %65, %66, %67, %68, %69, %70, %71, %72, %73, %74, %75, %76, %77, %78, %79}, %80, %81, p, 1, 1, 0, 1;\n}\n"
    :
      "+f"(d[0]), "+f"(d[1]), "+f"(d[2]), "+f"(d[3]), "+f"(d[4]), "+f"(d[5]), "+f"(d[6]), "+f"(d[7]),
      "+f"(d[8]), "+f"(d[9]), "+f"(d[10]), "+f"(d[11]), "+f"(d[12]), "+f"(d[13]), "+f"(d[14]), "+f"(d[15]),
      "+f"(d[16]), "+f"(d[17]), "+f"(d[18]), "+f"(d[19]), "+f"(d[20]), "+f"(d[21]), "+f"(d[22]), "+f"(d[23]),
      "+f"(d[24]), "+f"(d[25]), "+f"(d[26]), "+f"(d[27]), "+f"(d[28]), "+f"(d[29]), "+f"(d[30]), "+f"(d[31]),
      "+f"(d[32]), "+f"(d[33]), "+f"(d[34]), "+f"(d[35]), "+f"(d[36]), "+f"(d[37]), "+f"(d[38]), "+f"(d[39]),
      "+f"(d[40]), "+f"(d[41]), "+f"(d[42]), "+f"(d[43]), "+f"(d[44]), "+f"(d[45]), "+f"(d[46]), "+f"(d[47]),
      "+f"(d[48]), "+f"(d[49]), "+f"(d[50]), "+f"(d[51]), "+f"(d[52]), "+f"(d[53]), "+f"(d[54]), "+f"(d[55]),
      "+f"(d[56]), "+f"(d[57]), "+f"(d[58]), "+f"(d[59]), "+f"(d[60]), "+f"(d[61]), "+f"(d[62]), "+f"(d[63]),
      "+f"(d[64]), "+f"(d[65]), "+f"(d[66]), "+f"(d[67]), "+f"(d[68]), "+f"(d[69]), "+f"(d[70]), "+f"(d[71]),
      "+f"(d[72]), "+f"(d[73]), "+f"(d[74]), "+f"(d[75]), "+f"(d[76]), "+f"(d[77]), "+f"(d[78]), "+f"(d[79])
    : "l"(da), "l"(db), "r"(scale_d));
}
__device__ __forceinline__ void wgmma_ss_n64_tb0(float (&d)[32], uint64_t da, uint64_t db, int scale_d) {
  asm volatile("{\n.reg .pred p;\nsetp.ne.b32 p, %34, 0;\n"
      "wgmma.mma_async.sync.aligned.m64n64k16.f32.bf16.bf16 {"
      "%0, %1, %2, %3, %4, %5, %6, %7, %8, %9, %10, %11, %12, %13, %14, %15, "
      "%16, %17, %18, %19, %20, %21, %22, %23, %24, %25, %26, %27, %28, %29, %30, %31}, %32, %33, p, 1, 1, 0, 0;\n}\n"
    :
      "+f"(d[0]), "+f"(d[1]), "+f"(d[2]), "+f"(d[3]), "+f"(d[4]), "+f"(d[5]), "+f"(d[6]), "+f"(d[7]),
      "+f"(d[8]), "+f"(d[9]), "+f"(d[10]), "+f"(d[11]), "+f"(d[12]), "+f"(d[13]), "+f"(d[14]), "+f"(d[15]),
      "+f"(d[16]), "+f"(d[17]), "+f"(d[18]), "+f"(d[19]), "+f"(d[20]), "+f"(d[21]), "+f"(d[22]), "+f"(d[23]),
      "+f"(d[24]), "+f"(d[25]), "+f"(d[26]), "+f"(d[27]), "+f"(d[28]), "+f"(d[29]), "+f"(d[30]), "+f"(d[31])
    : "l"(da), "l"(db), "r"(scale_d));
}
__device__ __forceinline__ void wgmma_rs_n24_tb1(float (&d)[12], uint32_t a0, uint32_t a1, uint32_t a2, uint32_t a3, uint64_t db, int scale_d) {
  asm volatile("{\n.reg .pred p;\nsetp.ne.b32 p, %17, 0;\n"
      "wgmma.mma_async.sync.aligned.m64n24k16.f32.bf16.bf16 {"
      "%0, %1, %2, %3, %4, %5, %6, %7, %8, %9, %10, %11}, {%12, %13, %14, %15}, %16, p, 1, 1, 1;\n}\n"
    :
      "+f"(d[0]), "+f"(d[1]), "+f"(d[2]), "+f"(d[3]), "+f"(d[4]), "+f"(d[5]), "+f"(d[6]), "+f"(d[7]),
      "+f"(d[8]), "+f"(d[9]), "+f"(d[10]), "+f"(d[11])
    : "r"(a0), "r"(a1), "r"(a2), "r"(a3), "l"(db), "r"(scale_d));
}

__device__ __forceinline__ void bulk_g2s_mc(uint32_t dst, const void* src, uint32_t bytes, uint32_t bar, uint16_t mask) {
  asm volatile("cp.async.bulk.shared::cluster.global.mbarrier::complete_tx::bytes.multicast::cluster [%0], [%1], %2, [%3], %4;" ::"r"(dst), "l"(src), "r"(bytes), "r"(bar), "h"(mask) : "memory");
}
__device__ __forceinline__ void bulk_wait_all() { asm volatile("cp.async.bulk.wait_group 0;" ::: "memory"); }
__device__ __forceinline__ void fence_async_global() { asm volatile("fence.proxy.async.global;" ::: "memory"); }
__device__ __forceinline__ uint32_t ld_acquire(const uint32_t* p) { uint32_t v; asm volatile("ld.acquire.gpu.global.u32 %0, [%1];" : "=r"(v) : "l"(p) : "memory"); return v; }
__device__ __forceinline__ uint32_t ld_relaxed(const uint32_t* p) { uint32_t v; asm volatile("ld.relaxed.gpu.global.u32 %0, [%1];" : "=r"(v) : "l"(p) : "memory"); return v; }
__device__ __forceinline__ uint2 ld_relaxed_b64(const void* p) {
  unsigned long long v;
  asm volatile("ld.relaxed.gpu.global.b64 %0, [%1];" : "=l"(v) : "l"(p) : "memory");
  return make_uint2((uint32_t)v, (uint32_t)(v >> 32));
}
__device__ __forceinline__ uint4 ld_relaxed_v4(const void* p) { uint4 v; asm volatile("ld.relaxed.gpu.global.v4.u32 {%0, %1, %2, %3}, [%4];" : "=r"(v.x), "=r"(v.y), "=r"(v.z), "=r"(v.w) : "l"(p) : "memory"); return v; }
__device__ __forceinline__ void red_release(uint32_t* p) { asm volatile("red.release.gpu.global.add.u32 [%0], 1;" ::"l"(p) : "memory"); }
__device__ __forceinline__ void wait_flag(const uint32_t* p, uint32_t target) {
  uint32_t n = 0;
#pragma unroll 1
  while ((int32_t)(ld_acquire(p) - target) < 0) {
    if (++n > (1u << 21)) break;
  }
}
__device__ __forceinline__ uint4 lds128(uint32_t a) { uint4 v; asm volatile("ld.shared.v4.b32 {%0, %1, %2, %3}, [%4];" : "=r"(v.x), "=r"(v.y), "=r"(v.z), "=r"(v.w) : "r"(a) : "memory"); return v; }
__device__ __forceinline__ void sts128(uint32_t a, uint4 v) { asm volatile("st.shared.v4.b32 [%0], {%1, %2, %3, %4};" ::"r"(a), "r"(v.x), "r"(v.y), "r"(v.z), "r"(v.w) : "memory"); }
__device__ __forceinline__ uint32_t lds32(uint32_t a) { uint32_t v; asm volatile("ld.shared.b32 %0, [%1];" : "=r"(v) : "r"(a) : "memory"); return v; }
__device__ __forceinline__ float2 lds64f(uint32_t a) { float2 v; asm volatile("ld.shared.v2.f32 {%0, %1}, [%2];" : "=f"(v.x), "=f"(v.y) : "r"(a) : "memory"); return v; }
__device__ __forceinline__ uint32_t bf2_fma(uint32_t a, uint32_t b, uint32_t c) { uint32_t r; asm("fma.rn.bf16x2 %0, %1, %2, %3;" : "=r"(r) : "r"(a), "r"(b), "r"(c)); return r; }
__device__ __forceinline__ void stsm4_p(uint32_t addr, uint32_t r0, uint32_t r1, uint32_t r2, uint32_t r3, uint32_t on) {
  asm volatile("{\n.reg .pred p;\nsetp.ne.u32 p, %5, 0;\n@p stmatrix.sync.aligned.m8n8.x4.shared.b16 [%0], {%1, %2, %3, %4};\n}" ::"r"(addr), "r"(r0), "r"(r1), "r"(r2), "r"(r3), "r"(on) : "memory");
}
__device__ __forceinline__ void cp_async16(uint32_t dst, const void* src) { asm volatile("cp.async.cg.shared.global [%0], [%1], 16;" ::"r"(dst), "l"(src) : "memory"); }
__device__ __forceinline__ void cp_commit() { asm volatile("cp.async.commit_group;" ::: "memory"); }
template <int N> __device__ __forceinline__ void cp_wait() { asm volatile("cp.async.wait_group %0;" ::"n"(N) : "memory"); }
__device__ __forceinline__ int tid_now() { int t; asm volatile("mov.u32 %0, %%tid.x;" : "=r"(t)); return t; }
#define PHASE_IDS const int tid = tid_now(), warp = tid >> 5, lane = tid & 31; (void)warp; (void)lane
__device__ __forceinline__ void cluster_arrive_relaxed() { asm volatile("barrier.cluster.arrive.relaxed.aligned;" ::: "memory"); }
__device__ __forceinline__ void cluster_wait() { asm volatile("barrier.cluster.wait.aligned;" ::: "memory"); }
template <int N> __device__ __forceinline__ void reg_inc() { asm volatile("setmaxnreg.inc.sync.aligned.u32 %0;" ::"n"(N)); }
template <int N> __device__ __forceinline__ void reg_dec() { asm volatile("setmaxnreg.dec.sync.aligned.u32 %0;" ::"n"(N)); }
__device__ __forceinline__ float rcp_a(float x) { float y; asm("rcp.approx.ftz.f32 %0, %1;" : "=f"(y) : "f"(x)); return y; }
__device__ __forceinline__ float sqrt_a(float x) { float y; asm("sqrt.approx.ftz.f32 %0, %1;" : "=f"(y) : "f"(x)); return y; }
__device__ __forceinline__ float silu_bf(float cv) { return bf_round(cv * rcp_a(1.f + __expf(-cv))); }

__device__ __forceinline__ uint32_t exp2_pair_alu(float u0, float u1, uint32_t m7) {
  const uint32_t T = __byte_perm(__float_as_uint(u0), __float_as_uint(u1), 0x6521);
  uint32_t G, E, P;
  asm("lop3.b32 %0, %1, %2, 0x3F003F00, 0xEA;" : "=r"(G) : "r"(T), "r"(m7));
  asm("lop3.b32 %0, %1, %2, 0x00030003, 0xBA;" : "=r"(E) : "r"(T), "r"(m7));
  asm("fma.rn.bf16x2 %0, %1, %2, %3;" : "=r"(P) : "r"(T), "r"(G), "r"(E));
  return P;
}

constexpr int P1_B = 65536, P1_BSLOT = 36864;
constexpr int P0_SCR = P1_B + 3 * P1_BSLOT;
constexpr int P1_STG = 147456;
constexpr int P2_SZ = 196608, P2_SQ = 197632;
constexpr int P2_NS = 8, P2_SLOT = 4 * PIECE_B;
constexpr int P1_QT = 122880;
constexpr int P1_INITA = 3, P1_INIT = 2;
constexpr int P3_STAGES = 5, P3_STAGE_B = 8192 + 20480;
constexpr int P3_R = 196608;
constexpr int P4_STAGES = 4, P4_STAGE_B = 16384 + 24576;
constexpr int P4_STG = 172032;
constexpr int PRM = 222208;
constexpr int PRM_BARS = PRM, PRM_MOD = PRM + 768, PRM_RED = PRM_MOD + 2560, PRM_G3 = PRM_RED + 1024,
              PRM_G5 = PRM_G3 + 320, PRM_ST4 = PRM_G5 + 320, PRM_S12 = PRM_ST4 + 1024, PRM_EP = PRM_S12 + 3072, PRM_NRM = PRM_EP + 16,
              PRM_END = PRM_NRM + 64;
constexpr int MEGA_SMEM = PRM_END;
enum { B_FULL1 = 0, B_EMPTY1 = 4, B_FULL2 = 80, B_EMPTY2 = 88, B_SFREE = 8, B_QF = 18, B_QRDY = 17, B_GO2B = 19, B_FULL3 = 20, B_EMPTY3 = 26, B_R3 = 32,
       B_FULL4 = 34, B_X1S = 38, B_STS = 39, B_GO4 = 40, B_FULL5 = 41, B_EMPTY5 = 47, B_GO5 = 54, B_STG4 = 55, B_PRM3 = 56, B_PRM4 = 57,
       B_NORM = 58, B_HHG = 59, B_FULLA = 65, B_EMPTYA = 69, B_GO1 = 73, B_EMPTY4 = 74, B_PUB3 = 78, B_F5 = 63, B_RPK = 64, B_RPKD = 12, B_COUNT = 96 };
enum { C_EPOCH = 0, C_P0 = 1, C_MOD2 = 2, C_WP = 3, C_DONE = 4, C_PK = 5, C_KV = 8, C_X1 = 16, C_ST = 32, C_HH = 64, C_O = 160, C_COUNT = 224 };

struct Ptrs { const bf16 *x, *c, *wmod, *wg, *wu, *wo, *wd, *wqkv; };

__device__ __forceinline__ void aux_cta(const Ptrs& P, int a, uint32_t sbase, uint32_t ep1) {
  constexpr int DEPTH = 16;
  const int t = threadIdx.x;
  float* red = (float*)__cvta_shared_to_generic(sbase);
  uint32_t* c1s = (uint32_t*)__cvta_shared_to_generic(sbase + 32768);
  float* sbs = (float*)(c1s + DM);
  const uint32_t ring = sbase + 65536 + t * 16;
  if (t == 0) wait_flag(&g_sync[(C_P0) * 32], ep1 * 128);
  __syncthreads();
  const int cc = t % 96, rg = t / 96;
  const int tile = a * 2 + cc / 48, pass = (cc / 24) & 1, ch = cc % 24;
  const bf16* src = (ch >= 12 ? P.wu : P.wg) + pass * 768 + tile * 96 + (ch % 12) * 8;
  if (t < 480) {
#pragma unroll 1
    for (int i = 0; i < DEPTH; i++) { cp_async16(ring + i * 8192, src + (size_t)(rg + 5 * i) * FF); cp_commit(); }
  }
  if (t == 0) wait_flag(&g_sync[(C_MOD2) * 32], ep1 * 80);
  __syncthreads();
  for (int i = t; i < DM; i += 512) {
    const float cb = __bfloat162float(__ldcg(&g_mod[4 * DM + i]));
    c1s[i] = pack_bf16(1.f + cb, 1.f + cb);
    sbs[i] = __bfloat162float(__ldcg(&g_mod[3 * DM + i]));
  }
  __syncthreads();
  float s1[8], s2[8];
  if (t < 480) {
    unsigned char* dst = g_wp + (size_t)(tile * 2 + pass) * 10 * 24576 + (ch >> 3) * 8192;
#pragma unroll
    for (int j = 0; j < 8; j++) { s1[j] = 0.f; s2[j] = 0.f; }
#pragma unroll 2
    for (int k = rg, i = 0; k < DM; k += 5, i++) {
      cp_wait<DEPTH - 1>();
      const uint32_t slot = ring + (i & (DEPTH - 1)) * 8192;
      const uint4 w = lds128(slot);
      const uint32_t c1 = c1s[k];
      const float sb = sbs[k];
      uint4 o;
      o.x = bf2_mul(w.x, c1); o.y = bf2_mul(w.y, c1); o.z = bf2_mul(w.z, c1); o.w = bf2_mul(w.w, c1);
      s1[0] += bf_lo(o.x); s1[1] += bf_hi(o.x); s1[2] += bf_lo(o.y); s1[3] += bf_hi(o.y);
      s1[4] += bf_lo(o.z); s1[5] += bf_hi(o.z); s1[6] += bf_lo(o.w); s1[7] += bf_hi(o.w);
      s2[0] += sb * bf_lo(w.x); s2[1] += sb * bf_hi(w.x); s2[2] += sb * bf_lo(w.y); s2[3] += sb * bf_hi(w.y);
      s2[4] += sb * bf_lo(w.z); s2[5] += sb * bf_hi(w.z); s2[6] += sb * bf_lo(w.w); s2[7] += sb * bf_hi(w.w);
      *(uint4*)(dst + (size_t)(k >> 6) * 24576 + (k & 63) * 128 + (((ch & 7) ^ (k & 7)) << 4)) = o;
      if (k + 5 * DEPTH < DM) cp_async16(slot, src + (size_t)(k + 5 * DEPTH) * FF);
      cp_commit();
    }
#pragma unroll
    for (int j = 0; j < 8; j++) { red[(rg * 96 + cc) * 16 + j] = s1[j]; red[(rg * 96 + cc) * 16 + 8 + j] = s2[j]; }
  }
  __syncthreads();
#pragma unroll 1
  for (int i = t; i < 96 * 16; i += 512) {
    float v = 0.f;
#pragma unroll
    for (int r = 0; r < 5; r++) v += red[r * 96 * 16 + i];
    const int c2 = i >> 4, j = i & 15;
    const int tp = a * 4 + c2 / 24, ch2 = c2 % 24, col = (ch2 % 12) * 8 + (j & 7);
    g_s12[(tp * 48 + (col >> 1)) * 8 + (ch2 >= 12 ? 4 : 0) + (j >> 3) * 2 + (col & 1)] = v;
  }
  __syncthreads();
  if (t == 0) red_release(&g_sync[(C_WP) * 32]);
}

__global__ void __cluster_dims__(2, 1, 1) __launch_bounds__(512, 1)
k_mega(const __grid_constant__ CUtensorMap tm_xa, const __grid_constant__ CUtensorMap tm_wqkv,
       const __grid_constant__ CUtensorMap tm_wo, const __grid_constant__ CUtensorMap tm_xr,
       const __grid_constant__ CUtensorMap tm_x1r, const __grid_constant__ CUtensorMap tm_x1a,
       const __grid_constant__ CUtensorMap tm_hh, const __grid_constant__ CUtensorMap tm_wd,
       const __grid_constant__ CUtensorMap tm_out, const __grid_constant__ CUtensorMap tm_wkv,
       const __grid_constant__ CUtensorMap tm_hhs, const __grid_constant__ Ptrs P) {
  extern __shared__ __align__(1024) unsigned char smem_raw[];
  const uint32_t sbase = smem_u32(smem_raw);
  const uint32_t bars = sbase + PRM_BARS;
  const uint32_t rank = blockIdx.x & 1;
  const int wg = __shfl_sync(0xffffffff, threadIdx.x >> 7, 0);
  int pr;
  {
    const int p = blockIdx.x >> 1;
    int hg, idx;
    if (p < 4) { hg = 15; idx = p; }
    else if (p < 36) { hg = (p - 4) & 7; idx = (p - 4) >> 3; }
    else { hg = 8 + (p - 36) % 7; idx = (p - 36) / 7; }
    pr = p < 64 ? (hg >> 1) * 8 + (idx >> 1) * 4 + (hg & 1) * 2 + (idx & 1) : p;
  }
  const int bid = pr * 2 + (int)rank, G = pr >> 3, j8 = pr & 7;

  if (bid >= 128) {
    const uint32_t ep1 = __ldcg(&g_sync[(C_EPOCH) * 32]) + 1;
    aux_cta(P, bid - 128, sbase, ep1);
    if (threadIdx.x == 0) {
      const uint32_t old = atomicAdd(&g_sync[(C_DONE) * 32], 1u);
      if (old == ep1 * 132 - 1) g_sync[(C_EPOCH) * 32] = ep1;
    }
    return;
  }

  const int mt = 2 * G + rank;
  const int nt4 = j8 & 3, mt64 = 4 * G + 2 * (j8 >> 2) + rank;
  auto p1_load_a = [&](int kb) {
    const uint32_t fb = bars + 8 * (B_FULLA + (kb & 3));
    mbar_expect(fb, 16384);
    tma2d(sbase + (kb & 3) * 16384, &tm_xa, kb * 64, mt * 128, fb);
  };
  auto p1_load_b = [&](int kb) {
    const uint32_t st = sbase + P1_B + (kb & 3) * P1_BSLOT, fb = bars + 8 * (B_FULL1 + (kb & 3));
    mbar_expect(fb, P1_BSLOT);
    tma3d_mc(st + rank * 10240, &tm_wkv, 0, kb * 64 + rank * 32, 20 + j8 * 5, fb, 3);
    tma2d_mc(st + 20480 + rank * 8192, &tm_wqkv, rank * 320 + j8 * 40, kb * 64, fb, 3);
  };
  auto norm2 = [&](uint32_t addr) {
    const uint4 a = lds128(addr), b = lds128(addr + 2048);
    const uint32_t w8 = lds32(addr + 4096), w9 = lds32(addr + 4100);
    const uint32_t w[10] = {a.x, a.y, a.z, a.w, b.x, b.y, b.z, b.w, w8, w9};
    float acc = 0.f;
#pragma unroll
    for (int q = 0; q < 10; q++) { const float lo = bf_lo(w[q]), hi = bf_hi(w[q]); acc = fmaf(lo, lo, acc); acc = fmaf(hi, hi, acc); }
    if (acc != acc) acc = __int_as_float(0x7f800000);
    return acc;
  };
  {
    PHASE_IDS;
    if (tid == 384) { tmap_prefetch(&tm_xa); tmap_prefetch(&tm_wkv); tmap_prefetch(&tm_wqkv); }
    float cv[3];
    const bool domod = bid < 80;
#pragma unroll
    for (int i = 0; i < 3; i++) {
      const int row = (tid >> 1) + 256 * i;
      const bool ok = domod && row < DM;
      if (ok) cp_async16(sbase + P0_SCR + i * 8192 + tid * 16, P.wmod + (size_t)row * (6 * DM) + bid * 16 + (tid & 1) * 8);
      cv[i] = ok ? __bfloat162float(P.c[row]) : 0.f;
    }
    cp_commit();
    const int xrow = bid * 16 + warp;
    uint2 v[5];
#pragma unroll
    for (int i = 0; i < 5; i++) v[i] = __ldg((const uint2*)(P.x + (size_t)xrow * DM + i * 128 + lane * 4));
    const uint32_t ep1 = ld_relaxed(&g_sync[(C_EPOCH) * 32]) + 1;
    if (tid == 0) {
      for (int s = 0; s < 4; s++) { mbar_init(bars + 8 * (B_FULL1 + s), 1); mbar_init(bars + 8 * (B_EMPTY1 + s), 16); }
      for (int s = 0; s < P2_NS; s++) { mbar_init(bars + 8 * (B_FULL2 + s), 1); mbar_init(bars + 8 * (B_EMPTY2 + s), 16); }
      for (int s = 0; s < 4; s++) { mbar_init(bars + 8 * (B_FULLA + s), 1); mbar_init(bars + 8 * (B_EMPTYA + s), 8); }
      mbar_init(bars + 8 * B_QF, 1); mbar_init(bars + 8 * B_SFREE, 2); mbar_init(bars + 8 * B_QRDY, 1); mbar_init(bars + 8 * B_GO2B, 8); mbar_init(bars + 8 * B_GO1, 2);
      for (int s = 0; s < 6; s++) {
        mbar_init(bars + 8 * (B_FULL3 + s), 2); mbar_init(bars + 8 * (B_EMPTY3 + s), 4);
        mbar_init(bars + 8 * (B_FULL5 + s), 2); mbar_init(bars + 8 * (B_EMPTY5 + s), 8);
      }
      for (int s = 0; s < P4_STAGES; s++) { mbar_init(bars + 8 * (B_FULL4 + s), 2); mbar_init(bars + 8 * (B_EMPTY4 + s), 16); }
      mbar_init(bars + 8 * B_R3, 1); mbar_init(bars + 8 * B_PUB3, 1); mbar_init(bars + 8 * B_F5, 1); mbar_init(bars + 8 * B_RPK, 1); mbar_init(bars + 8 * B_RPKD, 1); mbar_init(bars + 8 * B_X1S, 4); mbar_init(bars + 8 * B_STS, 4);
      mbar_init(bars + 8 * B_NORM, 9); mbar_init(bars + 8 * B_GO4, 8); mbar_init(bars + 8 * B_GO5, 16);
      mbar_init(bars + 8 * B_STG4, 2); for (int i = 0; i < 4; i++) mbar_init(bars + 8 * (B_HHG + i), 4); mbar_init(bars + 8 * B_PRM3, 128); mbar_init(bars + 8 * B_PRM4, 128);
      fence_mbar_init();
    }
    __syncwarp();
    cluster_arrive_relaxed();
    if (warp == 12) {
      cluster_wait();
      if (tid == 384) {
#pragma unroll 1
        for (int it = 0; it < P1_INITA; it++) { p1_load_a(it); if (it < P1_INIT) p1_load_b(it); }
      }
      __syncwarp();
    }
    float sum = 0.f;
#pragma unroll
    for (int i = 0; i < 5; i++) sum += (bf_lo(v[i].x) + bf_hi(v[i].x)) + (bf_lo(v[i].y) + bf_hi(v[i].y));
    __syncwarp();
#pragma unroll
    for (int o = 16; o; o >>= 1) sum += __shfl_xor_sync(0xffffffff, sum, o);
    const float mean = sum * (1.f / DM);
    float sq = 0.f;
#pragma unroll
    for (int i = 0; i < 5; i++) {
      const float a = bf_lo(v[i].x) - mean, b = bf_hi(v[i].x) - mean, c = bf_lo(v[i].y) - mean, d = bf_hi(v[i].y) - mean;
      sq += a * a + b * b + c * c + d * d;
    }
#pragma unroll
    for (int o = 16; o; o >>= 1) sq += __shfl_xor_sync(0xffffffff, sq, o);
    if (lane == 0) {
      const float var = bf_round(sq * (1.f / DM));
      const float rs = bf_round(sqrt_a(bf_round(var + 1e-5f)));
      const unsigned long long word = ((unsigned long long)(pack_bf16(0.f, mean) | (ep1 & 0xFFFFu)) << 32) | __float_as_uint(rs);
      asm volatile("st.relaxed.gpu.global.b64 [%0], %1;" ::"l"(&g_st1[xrow]), "l"(word) : "memory");
    }
    if (domod) {
      float acc[8];
#pragma unroll
      for (int j = 0; j < 8; j++) acc[j] = 0.f;
#pragma unroll
      for (int i = 0; i < 3; i++) {
        const float sv = silu_bf(cv[i]);
        if (i == 0) cp_wait<0>();
        uint4 wv[3];
        wv[i] = (i < 2 || tid < 256) ? lds128(sbase + P0_SCR + i * 8192 + tid * 16) : make_uint4(0, 0, 0, 0);
        acc[0] = fmaf(sv, bf_lo(wv[i].x), acc[0]); acc[1] = fmaf(sv, bf_hi(wv[i].x), acc[1]);
        acc[2] = fmaf(sv, bf_lo(wv[i].y), acc[2]); acc[3] = fmaf(sv, bf_hi(wv[i].y), acc[3]);
        acc[4] = fmaf(sv, bf_lo(wv[i].z), acc[4]); acc[5] = fmaf(sv, bf_hi(wv[i].z), acc[5]);
        acc[6] = fmaf(sv, bf_lo(wv[i].w), acc[6]); acc[7] = fmaf(sv, bf_hi(wv[i].w), acc[7]);
      }
      const bool h16 = lane & 16, h8 = lane & 8, h4 = lane & 4;
      float b4[4], b2[2], b1;
#pragma unroll
      for (int j = 0; j < 4; j++) b4[j] = (h16 ? acc[4 + j] : acc[j]) + __shfl_xor_sync(0xffffffff, h16 ? acc[j] : acc[4 + j], 16);
#pragma unroll
      for (int j = 0; j < 2; j++) b2[j] = (h8 ? b4[2 + j] : b4[j]) + __shfl_xor_sync(0xffffffff, h8 ? b4[j] : b4[2 + j], 8);
      b1 = (h4 ? b2[1] : b2[0]) + __shfl_xor_sync(0xffffffff, h4 ? b2[0] : b2[1], 4);
      b1 += __shfl_xor_sync(0xffffffff, b1, 2);
      if (!(lane & 2)) sts32(sbase + PRM_RED + warp * 64 + ((lane & 1) * 8 + (lane >> 2)) * 4, __float_as_uint(b1));
    }
    if (tid == 32) sts64(sbase + PRM_EP, ep1, 0u);
    __syncthreads();
    if (tid == 384) { mbar_arrive_cluster(bars + 8 * B_GO1, 0); mbar_arrive_cluster(bars + 8 * B_GO1, 1); }
    if (warp == 0) {
      if (domod) {
        float s0 = 0.f;
#pragma unroll
        for (int w = 0; w < 8; w++) s0 += __uint_as_float(lds32(sbase + PRM_RED + ((lane >> 4) * 8 + w) * 64 + (lane & 15) * 4));
        s0 += __shfl_xor_sync(0xffffffff, s0, 16);
        if (lane < 16) asm volatile("st.relaxed.gpu.global.u32 [%0], %1;" ::"l"(&g_modt[bid * 16 + lane]), "r"(pack_bf16(0.f, s0) | (ep1 & 0xFFFFu)) : "memory");
      }
      if (lane == 0) asm volatile("red.relaxed.gpu.global.add.u32 [%0], 1;" ::"l"(&g_sync[(C_P0) * 32]) : "memory");
    }
  }

  {
    {
      PHASE_IDS;
      const uint32_t tag = lds32(sbase + PRM_EP) & 0xFFFFu;
      uint32_t n = 0;
      if (tid >= 256 && tid < 416) {
        const int t = tid - 256;
        uint4 lo, hi;
        do {
          lo = ld_relaxed_v4(&g_modt[t * 8]); hi = ld_relaxed_v4(&g_modt[t * 8 + 4]);
        } while ((((lo.x ^ tag) | (lo.y ^ tag) | (lo.z ^ tag) | (lo.w ^ tag) | (hi.x ^ tag) | (hi.y ^ tag) | (hi.z ^ tag) | (hi.w ^ tag)) & 0xFFFFu) && ++n < (1u << 21));
        uint4 v = make_uint4(__byte_perm(lo.x, lo.y, 0x7632), __byte_perm(lo.z, lo.w, 0x7632), __byte_perm(hi.x, hi.y, 0x7632), __byte_perm(hi.z, hi.w, 0x7632));
        if (t >= 80) { v.x = bf2_add(v.x, 0x3F803F80u); v.y = bf2_add(v.y, 0x3F803F80u); v.z = bf2_add(v.z, 0x3F803F80u); v.w = bf2_add(v.w, 0x3F803F80u); }
        const int ch = t < 80 ? t : t - 80;
        const uint32_t a = sbase + PRM_MOD + (ch >> 3) * 256 + (t < 80 ? 32 : 0) + (ch & 7) * 4;
        sts32(a, v.x); sts32(a + 64, v.y); sts32(a + 128, v.z); sts32(a + 192, v.w);
      }
      if (tid < 128) {
        uint2 s0;
        do {
          s0 = ld_relaxed_b64(&g_st1[mt * 128 + tid]);
        } while (((s0.y ^ tag) & 0xFFFFu) && ++n < (1u << 21));
        sts64(sbase + PRM_ST4 + tid * 8, __float_as_uint(rcp_a(__uint_as_float(s0.x))), __byte_perm(s0.x, s0.y, 0x7632));
      }
    }
    __syncthreads();
    if (wg < 2) {
      reg_inc<208>();
      PHASE_IDS;
      const int g = lane >> 2, c = lane & 3, w4 = warp & 3;
      const int lrow = wg * 64 + w4 * 16 + ((lane >> 3) & 1) * 8 + (lane & 7);
      const uint32_t abase = sbase + lrow * 128, ahi = lane >> 4, ar7 = lane & 7;
      float acc[80], qa[20], qb[20];
      {
        const uint32_t w0 = lds32(sbase + PRM_ST4 + (wg * 64 + w4 * 16 + g) * 8 + 4), w1 = lds32(sbase + PRM_ST4 + (wg * 64 + w4 * 16 + g + 8) * 8 + 4);
        const uint32_t mn0 = __byte_perm(w0, 0, 0x3232), sd0 = __byte_perm(w0, 0, 0x1010), mn1 = __byte_perm(w1, 0, 0x3232), sd1 = __byte_perm(w1, 0, 0x1010);
        uint32_t c1[8], sh[8];
        auto fetch_p = [&](int it) {
          const uint32_t pm = sbase + PRM_MOD + it * 256 + c * 64;
          const uint4 ca = lds128(pm), cb = lds128(pm + 16), sa = lds128(pm + 32), sb = lds128(pm + 48);
          c1[0] = ca.x; c1[1] = ca.y; c1[2] = ca.z; c1[3] = ca.w; c1[4] = cb.x; c1[5] = cb.y; c1[6] = cb.z; c1[7] = cb.w;
          sh[0] = sa.x; sh[1] = sa.y; sh[2] = sa.z; sh[3] = sa.w; sh[4] = sb.x; sh[5] = sb.y; sh[6] = sb.z; sh[7] = sb.w;
        };
        auto wait_a = [&](int it) { mbar_wait(bars + 8 * (B_FULLA + (it & 3)), (it >> 2) & 1); };
        auto fetch_a = [&](uint32_t (&a)[16], int it) {
#pragma unroll
          for (int ks = 0; ks < 4; ks++) ldsm4(abase + (it & 3) * 16384 + (((2 * ks + ahi) ^ ar7) << 4), a[4 * ks], a[4 * ks + 1], a[4 * ks + 2], a[4 * ks + 3]);
        };
        auto xform_a = [&](uint32_t (&a)[16], int it) {
#pragma unroll
          for (int i = 0; i < 8; i++) {
            a[2 * i] = bf2_fma(bf2_sub(a[2 * i], mn0), c1[i], bf2_mul(sh[i], sd0));
            a[2 * i + 1] = bf2_fma(bf2_sub(a[2 * i + 1], mn1), c1[i], bf2_mul(sh[i], sd1));
          }
          reg_fence(a);
          __syncwarp();
          if (lane == 0) mbar_arrive(bars + 8 * (B_EMPTYA + (it & 3)));
        };
        auto release = [&](int it) {
          if (it + 4 < 10 && lane < 2) mbar_arrive_cluster(bars + 8 * (B_EMPTY1 + (it & 3)), lane);
        };
        uint32_t a0[16], a1[16];
#pragma unroll
        for (int i = 0; i < 80; i++) acc[i] = 0.f;
#pragma unroll
        for (int i = 0; i < 20; i++) { qa[i] = 0.f; qb[i] = 0.f; }
        reg_fence(acc); reg_fence(qa); reg_fence(qb);
        auto mma = [&](uint32_t (&a)[16], int it) {
          const uint32_t st = sbase + P1_B + (it & 3) * P1_BSLOT;
          const uint64_t db = make_desc(st, 2048, 512, 2), dq = make_desc(st + 20480, 8192, 1024, 1);
          mbar_wait(bars + 8 * (B_FULL1 + (it & 3)), (it >> 2) & 1);
          named_bar(13 + wg, 256);
          wg_fence();
#pragma unroll
          for (int ks = 0; ks < 4; ks++) {
            wgmma_rs_n40_tb1(qa, a[4 * ks], a[4 * ks + 1], a[4 * ks + 2], a[4 * ks + 3], dq + ks * 128, 1);
            wgmma_rs_n40_tb1(qb, a[4 * ks], a[4 * ks + 1], a[4 * ks + 2], a[4 * ks + 3], dq + ks * 128 + (8192 >> 4), 1);
            wgmma_rs_n160_tb1(acc, a[4 * ks], a[4 * ks + 1], a[4 * ks + 2], a[4 * ks + 3], db + (ks >> 1) * (10240 >> 4) + (ks & 1) * 64, 1);
          }
          wg_commit();
          if (wg == 0 || it < 9) asm volatile("bar.arrive %0, 256;" ::"r"(14 - wg) : "memory");
        };
        if (wg == 1) asm volatile("bar.arrive 13, 256;" ::: "memory");
        fetch_p(0); wait_a(0); fetch_a(a0, 0);
        xform_a(a0, 0);
        fetch_p(1); wait_a(1);
#pragma unroll 1
        for (int i = 0; i < 10; i += 2) {
          const int i2 = i + 2 < 10 ? i + 2 : 9, i3 = i + 3 < 10 ? i + 3 : 9;
          fetch_a(a1, i + 1);
          mma(a0, i);
          wait_a(i2);
          xform_a(a1, i + 1);
          fetch_p(i2);
          wg_wait<0>(); reg_fence(a0);
          release(i);
          fetch_a(a0, i2);
          mma(a1, i + 1);
          wait_a(i3);
          if (i + 2 < 10) xform_a(a0, i + 2);
          fetch_p(i3);
          wg_wait<0>(); reg_fence(a1);
          release(i + 1);
        }
        reg_fence(acc); reg_fence(qa); reg_fence(qb);
      }
      if (lane == 0) mbar_arrive(bars + 8 * B_GO2B);
      uint32_t off[5];
#pragma unroll
      for (int j = 0; j < 5; j++) {
        const int col = 8 * j + 2 * c, hl = col >= 20 ? 1 : 0, d = col - 20 * hl;
        off[j] = sbase + hl * PIECE_B + (d >> 3) * 2048 + (wg * 64 + w4 * 16 + g) * 16 + (d & 7) * 2;
      }
      const int r = tid & 127;
      const bool prw = (POLYMASK >> (r >> 3)) & 1;
      const bool isk = j8 < 4;
      const float rs0 = __uint_as_float(lds32(sbase + PRM_ST4 + (wg * 64 + w4 * 16 + g) * 8)), rs1 = __uint_as_float(lds32(sbase + PRM_ST4 + (wg * 64 + w4 * 16 + g + 8) * 8));
      const float m0 = (isk && ((POLYMASK >> (wg * 8 + 2 * w4)) & 1)) ? 2.f * rs0 : rs0, m1 = (isk && ((POLYMASK >> (wg * 8 + 2 * w4 + 1)) & 1)) ? 2.f * rs1 : rs1;
#pragma unroll
      for (int j = 0; j < 20; j++) {
        const uint32_t a = P1_STG + off[j % 5] + (j / 5) * 2 * PIECE_B;
        sts32(a, pack_bf16(acc[4 * j] * m0, acc[4 * j + 1] * m0));
        sts32(a + 128, pack_bf16(acc[4 * j + 2] * m1, acc[4 * j + 3] * m1));
      }
      const uint32_t aug = isk ? (prw ? 0x3F803F80u : 0u) : 0x00003F80u;
#pragma unroll
      for (int i = 0; i < 4; i++) sts64(sbase + P1_STG + (wg * 4 + i) * PIECE_B + 2 * 2048 + r * 16 + 8, aug, (isk && prw) ? 0x00003F80u : 0u);
      fence_async_smem();
      asm volatile("bar.arrive 6, 288;" ::: "memory");
      named_bar(1, 256);
      {
        const float sc = (isk && prw) ? 0.25f : 1.f;
#pragma unroll 1
        for (int i = 0; i < 4; i++) {
          float v = norm2(sbase + P1_STG + (wg * 4 + i) * PIECE_B + r * 16) * sc;
#pragma unroll
          for (int of = 16; of; of >>= 1) v = fmaxf(v, __shfl_xor_sync(0xffffffff, v, of));
          if (lane == 0) sts32(sbase + PRM_RED + 512 + (wg * 4 + i) * 16 + w4 * 4, __float_as_uint(v));
        }
      }
      asm volatile("bar.arrive 4, 288;" ::: "memory");
      mbar_wait(bars + 8 * B_RPKD, 0);
      if (tid == 0) { mbar_expect(bars + 8 * B_QRDY, 2 * PIECE_B); mbar_arrive_cluster(bars + 8 * B_QF, rank ^ 1); }
      const float qs = 0.22360679774997896f * 1.4426950408889634f;
      const float q0 = qs * rs0, q1 = qs * rs1;
#pragma unroll
      for (int j = 0; j < 5; j++) {
        const int hl = 8 * j + 2 * c >= 20 ? 1 : 0;
        const bool keep = hl == (int)rank;
        const uint32_t a = off[j] + (keep ? P2_SQ : P1_QT - hl * PIECE_B), pst = keep ? 2 * PIECE_B : PIECE_B;
        sts32(a, pack_bf16(qa[4 * j] * q0, qa[4 * j + 1] * q0));
        sts32(a + 128, pack_bf16(qa[4 * j + 2] * q1, qa[4 * j + 3] * q1));
        sts32(a + pst, pack_bf16(qb[4 * j] * q0, qb[4 * j + 1] * q0));
        sts32(a + pst + 128, pack_bf16(qb[4 * j + 2] * q1, qb[4 * j + 3] * q1));
      }
      sts64(sbase + P2_SQ + (wg * 2 + rank) * PIECE_B + 2 * 2048 + r * 16 + 8, 0xC04D4440u, 0x00003BACu);
      sts64(sbase + P1_QT + wg * PIECE_B + 2 * 2048 + r * 16 + 8, 0xC04D4440u, 0x00003BACu);
      sts32(sbase + P2_SZ + tid * 4, 0u);
      fence_async_smem();
      reg_dec<128>();
      asm volatile("bar.arrive 3, 512;" ::: "memory");
      named_bar(1, 256);
      if (tid < 2) {
        mbar_wait(bars + 8 * B_QF, 0);
        asm volatile("{\n.reg .b32 d, m;\nmapa.shared::cluster.u32 d, %0, %4;\nmapa.shared::cluster.u32 m, %3, %4;\n"
                     "cp.async.bulk.shared::cluster.shared::cta.mbarrier::complete_tx::bytes [d], [%1], %2, [m];\n}"
                     ::"r"(sbase + P2_SQ + (tid * 2 + rank) * PIECE_B), "r"(sbase + P1_QT + tid * PIECE_B), "r"(PIECE_B), "r"(bars + 8 * B_QRDY), "r"(rank ^ 1) : "memory");
      }
      __syncwarp();
      mbar_wait(bars + 8 * B_QRDY, 0);
      if (tid == 0) mbar_arrive_cluster(bars + 8 * B_SFREE, rank ^ 1);
      float v = fmaxf(norm2(sbase + P2_SQ + wg * 2 * PIECE_B + r * 16), norm2(sbase + P2_SQ + (wg * 2 + 1) * PIECE_B + r * 16));
#pragma unroll
      for (int of = 16; of; of >>= 1) v = fmaxf(v, __shfl_xor_sync(0xffffffff, v, of));
      if (lane == 0) { sts32(sbase + PRM_NRM + warp * 4, __float_as_uint(v)); mbar_arrive(bars + 8 * B_NORM); }
      __syncwarp();
    } else {
      reg_dec<48>();
      PHASE_IDS;
      const int w4 = warp & 3;
      if (tid == 256) {
#pragma unroll 1
        for (int it = P1_INITA; it < 10; it++) { if (it >= 4) mbar_wait(bars + 8 * (B_EMPTYA + (it & 3)), ((it >> 2) - 1) & 1); p1_load_a(it); }
      } else if (tid == 288) {
#pragma unroll 1
        for (int it = P1_INIT; it < 10; it++) { mbar_wait(bars + 8 * (it >= 4 ? B_EMPTY1 + (it & 3) : B_GO1), it >= 4 ? ((it >> 2) - 1) & 1 : 0); p1_load_b(it); }
      } else if (tid == 320) {
        const uint32_t buf = sbase + P1_B + 4 * P1_BSLOT;
        uint32_t par = 0;
#pragma unroll 1
        for (int qi = 0; qi < (bid < 64 ? 5 : 4); qi++, par ^= 1) {
          const int q = bid + 128 * qi;
          const int nt = q / 144, r16 = q % 144;
          mbar_expect(bars + 8 * B_RPK, 5120);
          if (r16 < 48) {
#pragma unroll 1
            for (int e = 0; e < 2; e++) { const int ch = 2 * r16 + e; tma3d(buf + e * 2560, &tm_wo, 0, (ch / 3) * 20 + (ch % 3) * 8, nt * 5, bars + 8 * B_RPK); }
          } else {
            tma3d(buf, &tm_wd, 0, (r16 - 48) * 16, nt * 5, bars + 8 * B_RPK);
          }
          mbar_wait(bars + 8 * B_RPK, par);
          bulk_s2g(g_wpk + (size_t)q * 5120, buf, 5120);
          bulk_commit();
          bulk_wait_read();
        }
        mbar_arrive(bars + 8 * B_RPKD);
        bulk_wait_all();
        red_release(&g_sync[(C_PK) * 32]);
      } else if (wg == 3 && bid < 80) {
        const int t = tid & 127;
        const bf16* src = P.wmod + 1280 + bid * 32 + (t & 3) * 8;
        float acc[8];
#pragma unroll
        for (int j = 0; j < 8; j++) acc[j] = 0.f;
#pragma unroll 1
        for (int i0 = 0; i0 < 20; i0 += 4) {
          uint4 w[4]; float cv[4];
#pragma unroll
          for (int i = 0; i < 4; i++) {
            const int row = (t >> 2) + 32 * (i0 + i);
            asm volatile("ld.global.nc.L1::no_allocate.v4.u32 {%0, %1, %2, %3}, [%4];" : "=r"(w[i].x), "=r"(w[i].y), "=r"(w[i].z), "=r"(w[i].w) : "l"(src + (size_t)row * (6 * DM)));
            cv[i] = __bfloat162float(P.c[row]);
          }
#pragma unroll
          for (int i = 0; i < 4; i++) {
            const float sv = silu_bf(cv[i]);
            acc[0] = fmaf(sv, bf_lo(w[i].x), acc[0]); acc[1] = fmaf(sv, bf_hi(w[i].x), acc[1]);
            acc[2] = fmaf(sv, bf_lo(w[i].y), acc[2]); acc[3] = fmaf(sv, bf_hi(w[i].y), acc[3]);
            acc[4] = fmaf(sv, bf_lo(w[i].z), acc[4]); acc[5] = fmaf(sv, bf_hi(w[i].z), acc[5]);
            acc[6] = fmaf(sv, bf_lo(w[i].w), acc[6]); acc[7] = fmaf(sv, bf_hi(w[i].w), acc[7]);
          }
        }
        const bool h16 = lane & 16, h8 = lane & 8, h4 = lane & 4;
        float b4[4], b2[2], b1;
#pragma unroll
        for (int j = 0; j < 4; j++) b4[j] = (h16 ? acc[4 + j] : acc[j]) + __shfl_xor_sync(0xffffffff, h16 ? acc[j] : acc[4 + j], 16);
#pragma unroll
        for (int j = 0; j < 2; j++) b2[j] = (h8 ? b4[2 + j] : b4[j]) + __shfl_xor_sync(0xffffffff, h8 ? b4[j] : b4[2 + j], 8);
        b1 = (h4 ? b2[1] : b2[0]) + __shfl_xor_sync(0xffffffff, h4 ? b2[0] : b2[1], 4);
        sts32(sbase + PRM_RED + w4 * 128 + ((lane & 3) * 8 + (lane >> 2)) * 4, __float_as_uint(b1));
        named_bar(7, 128);
        if (w4 == 0) {
          float v = 0.f;
#pragma unroll
          for (int w = 0; w < 4; w++) v += __uint_as_float(lds32(sbase + PRM_RED + w * 128 + lane * 4));
          g_mod[1280 + bid * 32 + lane] = __float2bfloat16_rn(v);
          __syncwarp();
          if (lane == 0) red_release(&g_sync[(C_MOD2) * 32]);
        }
      }
      __syncwarp();
      if (warp == 8) {
        named_bar(6, 288);
        if (lane < 8) {
          bulk_s2g(g_kv + ((size_t)(((j8 & 3) * 8 + lane) * 16 + mt) * 2 + (j8 < 4 ? 0 : 1)) * PIECE_B, sbase + P1_STG + lane * PIECE_B, PIECE_B);
          bulk_commit();
        }
        __syncwarp();
        named_bar(4, 288);
        if (lane < 8) {
          const uint4 nv = lds128(sbase + PRM_RED + 512 + lane * 16);
          g_nrm[(j8 * 16 + mt) * 8 + lane] = __uint_as_float(max(max(nv.x, nv.y), max(nv.z, nv.w)));
          bulk_wait_all();
        }
        __syncwarp();
        if (lane == 0) { mbar_arrive(bars + 8 * B_SFREE); red_release(&g_sync[(C_KV + j8) * 32]); }

      } else if (warp == 9 || warp == 11) {
        mbar_wait(bars + 8 * B_GO2B, 0);
        if (lane < 4) wait_flag(&g_sync[(C_KV + 2 * lane + (j8 >> 2)) * 32], lds32(sbase + PRM_EP) * 16);
        __syncwarp();
        if (tid == 288) {
          const unsigned char* src = g_kv + (size_t)(2 * j8 + rank) * 16 * 2 * PIECE_B;
          fence_async_global();
#pragma unroll 1
          for (int q = 0; q < 2; q++) {
            mbar_expect(bars + 8 * (B_FULL2 + q), P2_SLOT);
            bulk_g2s(sbase + q * P2_SLOT, src + (size_t)q * P2_SLOT, P2_SLOT, bars + 8 * (B_FULL2 + q));
          }
        }
        __syncwarp();
        if (warp == 11) {
          const int hh = 2 * j8 + rank;
          const float* np = &g_nrm[(((lane >> 4) * 4 + (hh >> 3)) * 16 + (lane & 15)) * 8 + (hh & 7)];
          float v = fmaxf(__ldcg(np), __ldcg(np + 2 * 16 * 8));
#pragma unroll
          for (int of = 8; of; of >>= 1) v = fmaxf(v, __shfl_xor_sync(0xffffffff, v, of));
          if ((lane & 15) == 0) sts32(sbase + PRM_NRM + 32 + (lane >> 4) * 4, __float_as_uint(v));
          __syncwarp();
          if (lane == 0) mbar_arrive(bars + 8 * B_NORM);
      }
      }
      named_bar(3, 512);
      reg_inc<128>();
    }
  }

  {
    PHASE_IDS;
    const int w4 = warp & 3, tl = wg & 1, hs = wg >> 1;
    const uint32_t sZ = sbase + P2_SZ;
    const uint32_t zz = lds32(sbase + PRM_EP + 4);
    const uint32_t m7 = 0x007F007Fu + zz;
    float o[12];
    auto store_o = [&](int ph) {
      const int l2 = tid_now() & 31;
      float l0 = __shfl_sync(0xffffffff, o[8], (l2 & ~3) | 2), l1 = __shfl_sync(0xffffffff, o[10], (l2 & ~3) | 2);
      float r0 = rcp_a(l0), r1 = rcp_a(l1);
      uint32_t* t0 = (uint32_t*)g_o + (size_t)(((G * 4 + wg) * 32 + ph * 16 + 2 * j8 + rank) * 768 + w4 * 64 + l2);
      t0[0] = pack_bf16(o[0] * r0, o[1] * r0); t0[32] = pack_bf16(o[2] * r1, o[3] * r1);
      t0[256] = pack_bf16(o[4] * r0, o[5] * r0); t0[288] = pack_bf16(o[6] * r1, o[7] * r1);
      t0[512] = (l2 & 2) ? 0u : pack_bf16(o[8] * r0, o[9] * r0); t0[544] = (l2 & 2) ? 0u : pack_bf16(o[10] * r1, o[11] * r1);
      __syncwarp();
      if (ph && (tid_now() >> 5) != 15) asm volatile("bar.arrive 12, 512;" ::: "memory");
    };
    auto softmax = [&](float (&s)[32], uint32_t (&p)[16], const int half) {
#pragma unroll
      for (int n = 0; n < 8; n++) {
        if ((POLYMASK >> (half * 8 + n)) & 1) {
          p[2 * n] = exp2_pair_alu(s[4 * n], s[4 * n + 1], m7);
          p[2 * n + 1] = exp2_pair_alu(s[4 * n + 2], s[4 * n + 3], m7);
        } else {
          p[2 * n] = pack_bf16(ex2(s[4 * n]), ex2(s[4 * n + 1]));
          p[2 * n + 1] = pack_bf16(ex2(s[4 * n + 2]), ex2(s[4 * n + 3]));
        }
      }
      reg_fence(p);
    };
    auto pv = [&](uint32_t (&p)[16], uint64_t d, int sc) {
      wgmma_rs_n24_tb1(o, p[0], p[1], p[2], p[3], d, sc);
#pragma unroll
      for (int kk = 1; kk < 4; kk++) wgmma_rs_n24_tb1(o, p[4 * kk], p[4 * kk + 1], p[4 * kk + 2], p[4 * kk + 3], d + kk * 16, 1);
    };
    auto qk = [&](float (&s)[32], uint64_t dq0, uint64_t dq1, uint64_t d) {
      wgmma_ss_n64_tb0(s, dq0, d, 0);
      wgmma_ss_n64_tb0(s, dq1, d + (2048 >> 4), 1);
    };
    const int wu = __shfl_sync(0xffffffff, warp, 0);
    const uint32_t duty = wu == 0 ? 0x1110u : wu == 4 ? 0x0424u : wu == 8 ? 0x0241u : wu == 12 ? 0xC088u : 0u;
    auto recycle = [&](int gr) {
      asm volatile("{\n.reg .pred p;\nelect.sync _|p, 0xffffffff;\n@p mbarrier.arrive.shared::cta.b64 _, [%0];\n}" ::"r"(bars + 8 * B_EMPTY2 + (gr & 7) * 8) : "memory");
      if ((duty >> gr) & 1) {
        const int l = tid_now() & 31;
        mbar_wait<true>(gr ? bars + 8 * (B_EMPTY2 + ((gr - 1) & 7)) : bars + 8 * B_SFREE, gr ? ((gr - 1) >> 3) & 1 : 0);
        if (gr == 0) {
          mbar_wait<true>(bars + 8 * B_FULL2, 0);
          fence_async_global();
#pragma unroll 1
          for (int q = 2; q < 8; q++)
            asm volatile("{\n.reg .pred p;\nelect.sync _|p, 0xffffffff;\n@p mbarrier.arrive.expect_tx.shared::cta.b64 _, [%3], %2;\n"
                         "@p cp.async.bulk.shared::cluster.global.mbarrier::complete_tx::bytes [%0], [%1], %2, [%3];\n}"
                         ::"r"(sbase + q * P2_SLOT), "l"(g_kv + ((size_t)(2 * j8 + rank) * 8 + q) * P2_SLOT), "r"(P2_SLOT),
                           "r"(bars + 8 * (B_FULL2 + q)) : "memory");
        } else if (gr >= 14) {
          fence_async_global();
#pragma unroll 1
          for (int kb = (gr - 14) * 4; kb < gr - 10; kb++) {
            const uint32_t fb = bars + 8 * (B_FULL3 + kb), st = sbase + kb * P3_STAGE_B;
            asm volatile("{\n.reg .pred p;\nelect.sync _|p, 0xffffffff;\n"
                         "@p mbarrier.arrive.expect_tx.shared::cta.b64 _, [%2], 8192;\n@p mbarrier.arrive.expect_tx.shared::cta.b64 _, [%2], 20480;\n"
                         "@p cp.async.bulk.shared::cluster.global.mbarrier::complete_tx::bytes [%0], [%1], 8192, [%2];\n"
                         "@p cp.async.bulk.shared::cluster.global.mbarrier::complete_tx::bytes [%3], [%4], 20480, [%2];\n}"
                         ::"r"(st), "l"(g_o + ((size_t)mt64 * 12 + kb) * 8192), "r"(fb), "r"(st + 8192), "l"(g_wpk + ((size_t)nt4 * 36 + kb) * 20480) : "memory");
          }
        } else if (gr == 12) {
          if (l < 2) wait_flag(&g_sync[(l ? C_O + mt64 * 2 : C_PK) * 32], lds32(sbase + PRM_EP) * (l ? 16 : 128));
          __syncwarp();
        } else if (gr == 10) {
          if (l < 4) red_release(&g_sync[(C_O + (G * 4 + l) * 2) * 32]);
          __syncwarp();
        } else {
          fence_async_global();
          asm volatile("{\n.reg .pred p;\nelect.sync _|p, 0xffffffff;\n@p mbarrier.arrive.expect_tx.shared::cta.b64 _, [%3], %2;\n"
                       "@p cp.async.bulk.shared::cluster.global.mbarrier::complete_tx::bytes [%0], [%1], %2, [%3];\n}"
                       ::"r"(sbase + (gr - 2) * P2_SLOT), "l"(g_kv + ((size_t)(16 + 2 * j8 + rank) * 8 + gr - 2) * P2_SLOT), "r"(P2_SLOT),
                         "r"(bars + 8 * (B_FULL2 + gr - 2)) : "memory");
        }
      }
    };
    const uint64_t dK0 = make_desc(sbase, 2048, 128, 0), dV0 = make_desc(sbase + PIECE_B, 128, 2048, 0);
    constexpr int PC2 = 2 * PIECE_B >> 4;
    const uint32_t qa = sbase + P2_SQ + hs * PIECE_B + tl * 1024;
    const uint64_t dQa0 = make_desc(qa, 2048, 128, 0), dQa1 = make_desc(sZ, qa + 4096 - sZ, 128, 0);
    const uint64_t dQb0 = make_desc(qa + 2 * PIECE_B, 2048, 128, 0), dQb1 = make_desc(sZ, qa + 2 * PIECE_B + 4096 - sZ, 128, 0);
    mbar_wait<true>(bars + 8 * B_NORM, 0);
    bool safe;
    {
      const uint4 q0 = lds128(sbase + PRM_NRM), q1 = lds128(sbase + PRM_NRM + 16);
      const float2 kv = lds64f(sbase + PRM_NRM + 32);
      const float qm = __uint_as_float(max(max(max(q0.x, q0.y), max(q0.z, q0.w)), max(max(q1.x, q1.y), max(q1.z, q1.w))));
      safe = __all_sync(0xffffffff, qm * kv.x <= 64.f * 64.f && qm < 1e30f && kv.x < 1e30f && kv.y < 1e30f);
    }
#pragma unroll
    for (int i = 0; i < 12; i++) o[i] = 0.f;
    if (safe) {
      float s0[32], s1[32]; uint32_t p[16];
#pragma unroll
      for (int i = 0; i < 32; i++) { s0[i] = 0.f; s1[i] = 0.f; }
      reg_fence(s0); reg_fence(s1); reg_fence(o);
      mbar_wait<true>(bars + 8 * B_FULL2, 0);
      wg_fence(); qk(s0, dQa0, dQa1, dK0); wg_commit(); qk(s1, dQa0, dQa1, dK0 + 64); wg_commit();
      constexpr uint64_t VK = (uint64_t)(PIECE_B >> 4) + ((uint64_t)(128 >> 4) << 16) + ((uint64_t)(2048 >> 4) << 32) - ((uint64_t)(2048 >> 4) << 16) - ((uint64_t)(128 >> 4) << 32);
      auto group = [&](int gr, uint64_t k, uint64_t q0, uint64_t q1, uint64_t kn, uint64_t qn0, uint64_t qn1, uint32_t fbar, uint32_t fpar, int acc_o) {
        const uint64_t v = k + VK;
        wg_wait<1>(); reg_fence(s0); reg_fence(o);
        recycle(gr);
        softmax(s0, p, 0);
        wg_fence(); pv(p, v, acc_o); wg_commit(); qk(s0, q0, q1, k + PC2); wg_commit();
        wg_wait<1>(); reg_fence(s1); reg_fence(o);
        softmax(s1, p, 1);
        wg_fence(); pv(p, v + 64, 1); wg_commit(); qk(s1, q0, q1, k + PC2 + 64); wg_commit();
        wg_wait<1>(); reg_fence(s0); reg_fence(o);
        softmax(s0, p, 0);
        mbar_wait<true>(fbar, fpar);
        wg_fence(); pv(p, v + PC2, 1); wg_commit(); qk(s0, qn0, qn1, kn); wg_commit();
        wg_wait<1>(); reg_fence(s1); reg_fence(o);
        softmax(s1, p, 1);
        wg_fence(); pv(p, v + PC2 + 64, 1); wg_commit(); qk(s1, qn0, qn1, kn + 64); wg_commit();
      };
#pragma unroll 1
      for (int ph = 0; ph < 2; ph++) {
        const uint64_t q0 = ph ? dQb0 : dQa0, q1 = ph ? dQb1 : dQa1;
        uint64_t k = dK0;
#pragma unroll 1
        for (int g8 = 0; g8 < 7; g8++, k += P2_SLOT >> 4)
          group(ph * 8 + g8, k, q0, q1, k + (P2_SLOT >> 4), q0, q1, bars + 8 * (B_FULL2 + 1) + g8 * 8, ph, g8);
        group(ph * 8 + 7, k, q0, q1, dK0, dQb0, dQb1, bars + 8 * B_FULL2, 1, 1);
        wg_wait<1>(); reg_fence(o);
        store_o(ph);
      }
      wg_wait<0>(); reg_fence(o); reg_fence(s0); reg_fence(s1);
    } else {
      if ((tid & 127) < 64) {
        sts64(qa + 4096 + (tid & 63) * 16 + 8, 0u, 0u);
        sts64(qa + 2 * PIECE_B + 4096 + (tid & 63) * 16 + 8, 0u, 0u);
      }
      fence_async_smem();
      named_bar(8 + wg, 128);
      float m0 = -INFINITY, m1 = -INFINITY;
      float s[32]; uint32_t p[16];
#pragma unroll
      for (int i = 0; i < 32; i++) s[i] = 0.f;
#pragma unroll 1
      for (int b = 0; b < 64; b++) {
        const int gr = b >> 2;
        if (!(b & 3)) {
          if (gr == 8) {
            store_o(0);
            m0 = m1 = -INFINITY;
#pragma unroll
            for (int i = 0; i < 12; i++) o[i] = 0.f;
          }
          recycle(gr);
          mbar_wait<true>(bars + 8 * (B_FULL2 + (gr & 7)), gr >> 3);
        }
        const uint64_t off = (uint64_t)((b & 1) * 64 + ((b >> 1) & 1) * PC2 + (gr & 7) * (P2_SLOT >> 4));
        reg_fence(s); reg_fence(o);
        wg_fence(); qk(s, gr < 8 ? dQa0 : dQb0, gr < 8 ? dQa1 : dQb1, dK0 + off); wg_commit(); wg_wait<0>(); reg_fence(s);
        float b0 = -INFINITY, b1 = -INFINITY;
#pragma unroll
        for (int n = 0; n < 8; n++) {
          const float f = ((POLYMASK >> ((b & 1) * 8 + n)) & 1) ? 0.5f : 1.f;
          s[4 * n] *= f; s[4 * n + 1] *= f; s[4 * n + 2] *= f; s[4 * n + 3] *= f;
          b0 = fmaxf(b0, fmaxf(s[4 * n], s[4 * n + 1])); b1 = fmaxf(b1, fmaxf(s[4 * n + 2], s[4 * n + 3]));
        }
        b0 = fmaxf(b0, __shfl_xor_sync(0xffffffff, b0, 1)); b0 = fmaxf(b0, __shfl_xor_sync(0xffffffff, b0, 2));
        b1 = fmaxf(b1, __shfl_xor_sync(0xffffffff, b1, 1)); b1 = fmaxf(b1, __shfl_xor_sync(0xffffffff, b1, 2));
        const float n0 = fmaxf(m0, b0), n1 = fmaxf(m1, b1);
        const float f0 = ex2(m0 - n0), f1 = ex2(m1 - n1);
        m0 = n0; m1 = n1;
#pragma unroll
        for (int jj = 0; jj < 3; jj++) { o[4 * jj] *= f0; o[4 * jj + 1] *= f0; o[4 * jj + 2] *= f1; o[4 * jj + 3] *= f1; }
#pragma unroll
        for (int n = 0; n < 8; n++) {
          p[2 * n] = pack_bf16(ex2(s[4 * n] - m0), ex2(s[4 * n + 1] - m0));
          p[2 * n + 1] = pack_bf16(ex2(s[4 * n + 2] - m1), ex2(s[4 * n + 3] - m1));
        }
        reg_fence(p); reg_fence(o);
        wg_fence(); pv(p, dV0 + off, 1); wg_commit(); wg_wait<0>(); reg_fence(o);
      }
      store_o(1);
    }
  }

  if (wg < 2) {
    reg_inc<224>();
    PHASE_IDS;
#pragma unroll 1
    for (uint32_t ph = 0; ph < 3; ph++) {
      if (wg == (ph == 0 ? 1 : 0)) {
        const uint32_t full = bars + 8 * (ph == 2 ? B_FULL5 : B_FULL3), empty = bars + 8 * (ph == 2 ? B_EMPTY5 : B_EMPTY3);
        const int KB = ph == 0 ? 0 : (ph == 1 ? 12 : 24), NS = ph == 2 ? P3_STAGES : 6;
        float acc[80];
#pragma unroll
        for (int i = 0; i < 80; i++) acc[i] = 0.f;
        reg_fence(acc);
        int s = 0, par = 0;
#pragma unroll 1
        for (int kb = 0; kb < KB; kb++) {
          const uint32_t st = sbase + s * P3_STAGE_B;
          mbar_wait(full + 8 * s, par);
          const uint64_t da = ph == 2 ? make_desc(st, 16, 1024, 1) : make_desc(st, 1024, 128, 0);
          const uint64_t db = ph == 2 ? make_desc(st + 8192, 1024, 512, 2) : make_desc(st + 8192, 512, 2560, 2);
          const uint32_t astep = ph == 2 ? 2 : 128;
          wg_fence();
#pragma unroll
          for (int ks = 0; ks < 4; ks++) wgmma_ss_n160_tb1(acc, da + ks * astep, db + ks * (5120 >> 4), 1);
          wg_commit();
          if (kb > 0) {
            wg_wait<1>();
            if (ph == 2) { if (kb - 1 + NS < KB && lane < 2) mbar_arrive_cluster(empty + 8 * (s == 0 ? NS - 1 : s - 1), lane); }
            else if (lane == 0) mbar_arrive(empty + 8 * (s == 0 ? NS - 1 : s - 1));
          }
          if (++s == NS) { s = 0; par ^= 1; }
        }
        wg_wait<0>();
        reg_fence(acc);
        if (ph == 1 && lane < 2) mbar_arrive_cluster(bars + 8 * B_GO4, lane);
        if (ph) { mbar_wait(bars + 8 * B_R3, 0); mbar_wait(bars + 8 * B_PRM3, 0); }
        const uint32_t sR = sbase + P3_R, gate_smem = sbase + (ph == 2 ? PRM_G5 : PRM_G3);
        const int m = lane >> 3, row = (warp & 3) * 16 + (m & 1) * 8 + (lane & 7), c = lane & 3;
        const uint32_t rowaddr = sR + row * 64;
        const int sw = (row >> 1) & 3;
        uint32_t xv[40];
#pragma unroll
        for (int j = 0; j < 20; j += 2) {
          const int tile = j + (m >> 1);
          const uint32_t a = rowaddr + (tile >> 2) * 4096 + (((tile & 3) ^ sw) << 4);
          uint32_t r0, r1, r2, r3;
          ldsm4(a, r0, r1, r2, r3);
          const uint32_t g0 = lds32(gate_smem + j * 16 + c * 4), g1 = lds32(gate_smem + j * 16 + 16 + c * 4);
          r0 = bf2_add(r0, bf2_mul(g0, pack_bf16(acc[4 * j], acc[4 * j + 1])));
          r1 = bf2_add(r1, bf2_mul(g0, pack_bf16(acc[4 * j + 2], acc[4 * j + 3])));
          r2 = bf2_add(r2, bf2_mul(g1, pack_bf16(acc[4 * j + 4], acc[4 * j + 5])));
          r3 = bf2_add(r3, bf2_mul(g1, pack_bf16(acc[4 * j + 6], acc[4 * j + 7])));
          stsm4_p(a, r0, r1, r2, r3, ph);
          xv[2 * j] = r0; xv[2 * j + 1] = r1; xv[2 * j + 2] = r2; xv[2 * j + 3] = r3;
        }
        fence_async_smem();
        __syncwarp();
        if (lane == 0 && ph) mbar_arrive(bars + 8 * B_X1S);
        if (ph < 2) {
          float s0 = 0.f, s1 = 0.f;
#pragma unroll
          for (int i = 0; i < 20; i++) { s0 += bf_lo(xv[2 * i]) + bf_hi(xv[2 * i]); s1 += bf_lo(xv[2 * i + 1]) + bf_hi(xv[2 * i + 1]); }
          s0 += __shfl_xor_sync(0xffffffff, s0, 1); s0 += __shfl_xor_sync(0xffffffff, s0, 2);
          s1 += __shfl_xor_sync(0xffffffff, s1, 1); s1 += __shfl_xor_sync(0xffffffff, s1, 2);
          const float m0 = s0 * (1.f / 160.f), m1 = s1 * (1.f / 160.f);
          float q0 = 0.f, q1 = 0.f;
#pragma unroll
          for (int i = 0; i < 20; i++) {
            const float a = bf_lo(xv[2 * i]) - m0, b = bf_hi(xv[2 * i]) - m0, d = bf_lo(xv[2 * i + 1]) - m1, e = bf_hi(xv[2 * i + 1]) - m1;
            q0 = fmaf(a, a, q0); q0 = fmaf(b, b, q0); q1 = fmaf(d, d, q1); q1 = fmaf(e, e, q1);
          }
          q0 += __shfl_xor_sync(0xffffffff, q0, 1); q0 += __shfl_xor_sync(0xffffffff, q0, 2);
          q1 += __shfl_xor_sync(0xffffffff, q1, 1); q1 += __shfl_xor_sync(0xffffffff, q1, 2);
          if (c == 0 && ph) {
            const int r = mt64 * 64 + warp * 16 + (lane >> 2);
            g_st2[nt4 * S_LEN + r] = make_float2(m0, q0);
            g_st2[nt4 * S_LEN + r + 8] = make_float2(m1, q1);
          }
          __syncwarp();
          if (lane == 0 && ph) mbar_arrive(bars + 8 * B_STS);
        }
      }
      if (ph == 1) {
        float a1[96], a2[96];
#pragma unroll
        for (int i = 0; i < 96; i++) { a1[i] = 0.f; a2[i] = 0.f; }
        reg_fence(a1); reg_fence(a2);
        auto step = [&](float (&acc)[96], int it) {
          const uint32_t st = sbase + (it & 3) * P4_STAGE_B;
          mbar_wait(bars + 8 * (B_FULL4 + (it & 3)), (it >> 2) & 1);
          const uint64_t da = make_desc(st + wg * 8192, 16, 1024, 1), db = make_desc(st + 16384, 8192, 1024, 1);
          wg_fence();
#pragma unroll
          for (int ks = 0; ks < 4; ks++) wgmma_ss_n192_tb1(acc, da + ks * 2, db + ks * 128, 1);
          wg_commit();
          wg_wait<1>();
          if (it > 0 && lane < 2) mbar_arrive_cluster(bars + 8 * (B_EMPTY4 + ((it - 1) & 3)), lane);
        };
        const int m = lane >> 3, w4 = warp & 3, row = w4 * 16 + (m & 1) * 8 + (lane & 7), c = lane & 3;
        const uint32_t rowaddr = sbase + P4_STG + wg * 12288 + row * 64;
        const uint32_t stp = sbase + PRM_ST4 + (wg * 64 + w4 * 16 + (lane >> 2)) * 8;
        auto slice = [&](float (&acc)[96], int pass, int q) {
          const float2 sA = lds64f(stp), sB = lds64f(stp + 64);
          uint32_t r[4];
#pragma unroll
          for (int e = 0; e < 2; e++) {
            const int jj = 2 * q + e;
            const uint4 gp = lds128(sbase + PRM_S12 + pass * 1536 + (jj * 4 + c) * 32), up = lds128(sbase + PRM_S12 + pass * 1536 + (jj * 4 + c) * 32 + 16);
            const float g1x = __uint_as_float(gp.x), g1y = __uint_as_float(gp.y), g2x = __uint_as_float(gp.z), g2y = __uint_as_float(gp.w);
            const float u1x = __uint_as_float(up.x), u1y = __uint_as_float(up.y), u2x = __uint_as_float(up.z), u2y = __uint_as_float(up.w);
            const float ga0 = fmaf(sA.x, acc[4 * jj], fmaf(sA.y, g1x, g2x)), ga1 = fmaf(sA.x, acc[4 * jj + 1], fmaf(sA.y, g1y, g2y));
            const float gb0 = fmaf(sB.x, acc[4 * jj + 2], fmaf(sB.y, g1x, g2x)), gb1 = fmaf(sB.x, acc[4 * jj + 3], fmaf(sB.y, g1y, g2y));
            const float ua0 = fmaf(sA.x, acc[48 + 4 * jj], fmaf(sA.y, u1x, u2x)), ua1 = fmaf(sA.x, acc[48 + 4 * jj + 1], fmaf(sA.y, u1y, u2y));
            const float ub0 = fmaf(sB.x, acc[48 + 4 * jj + 2], fmaf(sB.y, u1x, u2x)), ub1 = fmaf(sB.x, acc[48 + 4 * jj + 3], fmaf(sB.y, u1y, u2y));
            r[2 * e] = bf2_mul(pack_bf16(ga0, ga1), pack_bf16(ua0, ua1));
            r[2 * e + 1] = bf2_mul(pack_bf16(gb0, gb1), pack_bf16(ub0, ub1));
          }
          const int tile = 2 * q + (m >> 1);
          stsm4(rowaddr + (tile >> 2) * 4096 + (((tile & 3) ^ ((row >> 1) & 3)) << 4), r[0], r[1], r[2], r[3]);
          if (q == 5) {
            fence_async_smem();
            __syncwarp();
            if (lane == 0) mbar_arrive(bars + 8 * (B_HHG + pass * 2 + wg));
          }
        };
#pragma unroll 1
        for (int it = 0; it < 10; it++) step(a1, it);
        mbar_wait(bars + 8 * B_PRM4, 0);
#pragma unroll
        for (int it = 10; it < 13; it++) {
          step(a2, it);
          if (it == 10) reg_fence(a1);
          slice(a1, 0, 2 * (it - 10));
          slice(a1, 0, 2 * (it - 10) + 1);
        }
#pragma unroll 1
        for (int it = 13; it < 20; it++) step(a2, it);
        wg_wait<0>();
        reg_fence(a2);
        if (lane < 2) mbar_arrive_cluster(bars + 8 * B_GO5, lane);
        mbar_wait(bars + 8 * B_STG4, 0);
#pragma unroll
        for (int q = 0; q < 6; q++) slice(a2, 1, q);
      }
    }
  } else if (wg == 2) {
    reg_dec<32>();
    PHASE_IDS;
    const int t = tid & 127;
    const uint32_t ep1 = lds32(sbase + PRM_EP);
    if (t == 0) wait_flag(&g_sync[(C_MOD2) * 32], ep1 * 80);
    named_bar(2, 128);
    if (t < 80) {
      sts32(sbase + PRM_G3 + t * 4, __ldcg((const uint32_t*)(g_mod + 2 * DM + nt4 * 160 + t * 2)));
      sts32(sbase + PRM_G5 + t * 4, __ldcg((const uint32_t*)(g_mod + 5 * DM + nt4 * 160 + t * 2)));
    }
    mbar_arrive(bars + 8 * B_PRM3);
    if (t == 0) wait_flag(&g_sync[(C_WP) * 32], ep1 * 4);
    named_bar(2, 128);
    for (int i = t; i < 192; i += 128) sts128(sbase + PRM_S12 + i * 16, __ldcg((const uint4*)(g_s12 + j8 * 768 + i * 4)));
    if (t == 0) wait_flag(&g_sync[(C_ST + mt) * 32], ep1 * 8);
    named_bar(2, 128);
    {
      const float2* sp = &g_st2[mt * 128 + t];
      const float2 p0 = __ldcg(sp), p1 = __ldcg(sp + S_LEN), p2 = __ldcg(sp + 2 * S_LEN), p3 = __ldcg(sp + 3 * S_LEN);
      const float4 a = make_float4(p0.x, p0.y, p1.x, p1.y), b = make_float4(p2.x, p2.y, p3.x, p3.y);
      const float mean = (a.x + a.z + b.x + b.z) * 0.25f;
      const float d0 = a.x - mean, d1 = a.z - mean, d2 = b.x - mean, d3 = b.z - mean;
      const float m2 = (a.y + a.w + b.y + b.w) + 160.f * (d0 * d0 + d1 * d1 + d2 * d2 + d3 * d3);
      const float var = bf_round(m2 * (1.f / DM));
      const float rs = rcp_a(bf_round(sqrt_a(bf_round(var + 1e-5f))));
      asm volatile("st.shared.v2.f32 [%0], {%1, %2};" ::"r"(sbase + PRM_ST4 + t * 8), "f"(rs), "f"(-bf_round(mean) * rs) : "memory");
    }
    mbar_arrive(bars + 8 * B_PRM4);
    if ((t & 31) == 0 && t < 64) {
      const int w = t >> 5;
      tmap_prefetch(&tm_hhs);
#pragma unroll 1
      for (int pass = 0; pass < 2; pass++) {
        mbar_wait(bars + 8 * (B_HHG + pass * 2 + w), 0);
        tma3d_store(&tm_hhs, 0, mt * 128 + w * 64, pass * 24 + j8 * 3, sbase + P4_STG + w * 12288);
        bulk_commit();
        if (pass == 0) { bulk_wait_read(); mbar_arrive(bars + 8 * B_STG4); }
        bulk_wait_all();
        red_release(&g_sync[(C_HH + (mt * 2 + w) * 2 + pass) * 32]);
      }
    }
  } else {
    reg_dec<32>();
    PHASE_IDS;
    if (warp == 15) {
      named_bar(12, 512);
      if (lane < 4) red_release(&g_sync[(C_O + (G * 4 + lane) * 2 + 1) * 32]);
      if (lane == 0) {
        mbar_arrive(bars + 8 * B_PUB3);
        mbar_wait(bars + 8 * B_STS, 0);
        red_release(&g_sync[(C_ST + (mt64 >> 1)) * 32]);
        mbar_wait(bars + 8 * B_GO5, 0);
        wait_flag(&g_sync[(C_HH + mt64 * 2 + 1) * 32], lds32(sbase + PRM_EP) * 8);
        mbar_arrive(bars + 8 * B_F5);
      }
    } else if (tid == 448) {
      tmap_prefetch(&tm_x1r);
      mbar_wait(bars + 8 * B_X1S, 0);
      tma3d_store(&tm_x1r, 0, mt64 * 64, nt4 * 5, sbase + P3_R);
      bulk_commit();
      bulk_wait_all();
      red_release(&g_sync[(C_X1 + (mt64 >> 1)) * 32]);
      mbar_wait(bars + 8 * B_GO5, 0);
      tmap_prefetch(&tm_out);
      mbar_wait(bars + 8 * B_X1S, 1);
      tma3d_store(&tm_out, 0, mt64 * 64, nt4 * 5, sbase + P3_R);
      bulk_commit();
      const uint32_t ep1 = lds32(sbase + PRM_EP);
      const uint32_t old = atomicAdd(&g_sync[(C_DONE) * 32], 1u);
      if (old == ep1 * 132 - 1) g_sync[(C_EPOCH) * 32] = ep1;
      bulk_wait_read();
    } else if (tid == 384) {
      const uint32_t ep1 = lds32(sbase + PRM_EP);
#pragma unroll 1
      for (int ph = 1; ph < 3; ph++) {
        {
          const uint32_t full = bars + 8 * (ph == 2 ? B_FULL5 : B_FULL3), empty = bars + 8 * (ph == 2 ? B_EMPTY5 : B_EMPTY3);
          const unsigned char* img = g_wpk + ((size_t)nt4 * 36 + (ph == 2 ? 12 : 0)) * 20480;
          const int KB = ph == 2 ? 24 : 12, NS = ph == 2 ? P3_STAGES : 6;
          if (ph == 1) mbar_wait(bars + 8 * B_PUB3, 0);
          fence_async_global();
          int s = ph == 2 ? 0 : 5, par = 1;
#pragma unroll 1
          for (int kb = s; kb < KB; kb++) {
            if (kb >= NS) mbar_wait(empty + 8 * s, par);
            else if (ph == 2) mbar_wait(bars + 8 * (kb < 3 ? B_EMPTY4 + kb : B_GO5), 0);
            mbar_expect(full + 8 * s, 20480);
            bulk_g2s(sbase + s * P3_STAGE_B + 8192, img + (size_t)kb * 20480, 20480, full + 8 * s);
            if (++s == NS) { s = 0; par ^= 1; }
          }
        }
        if (ph == 1) {
          wait_flag(&g_sync[(C_WP) * 32], ep1 * 4);
          fence_async_global();
          mbar_wait(bars + 8 * B_GO4, 0);
          const unsigned char* wp = g_wp + (size_t)j8 * 20 * 24576;
#pragma unroll 1
          for (int it = 0; it < 20; it++) {
            const uint32_t fb = bars + 8 * (B_FULL4 + (it & 3));
            if (it >= P4_STAGES) mbar_wait(bars + 8 * (B_EMPTY4 + (it & 3)), ((it >> 2) - 1) & 1);
            mbar_expect(fb, 24576);
            bulk_g2s_mc(sbase + (it & 3) * P4_STAGE_B + 16384 + rank * 12288, wp + (size_t)it * 24576 + rank * 12288, 12288, fb, 3);
          }
        }
      }
    } else if (tid == 416) {
      const uint32_t ep1 = lds32(sbase + PRM_EP);
#pragma unroll 1
      for (int ph = 1; ph < 3; ph++) {
        {
          const uint32_t full = bars + 8 * (ph == 2 ? B_FULL5 : B_FULL3), empty = bars + 8 * (ph == 2 ? B_EMPTY5 : B_EMPTY3);
          tmap_prefetch(ph == 2 ? &tm_hh : &tm_xr);
          const int KB = ph == 2 ? 24 : 12, NS = ph == 2 ? P3_STAGES : 6;
          int s = ph == 2 ? 0 : 5, par = 1;
#pragma unroll 1
          for (int kb = s; kb < KB; kb++) {
            if (kb == 0 || kb == KB / 2) {
              if (ph == 2 && kb) mbar_wait(bars + 8 * B_F5, 0); else if (ph == 2) wait_flag(&g_sync[(C_HH + mt64 * 2) * 32], ep1 * 8); else wait_flag(&g_sync[(C_O + mt64 * 2 + (kb ? 1 : 0)) * 32], ep1 * 16);
              fence_async_global();
            }
            if (ph == 1 && kb == 5) { mbar_wait(bars + 8 * B_PUB3, 0); fence_async_global(); }
            if (kb >= NS) mbar_wait(empty + 8 * s, par);
            else if (ph == 2) mbar_wait(bars + 8 * (kb < 3 ? B_EMPTY4 + kb : B_GO5), 0);
            mbar_expect(full + 8 * s, 8192);
            if (ph == 2) tma2d(sbase + s * P3_STAGE_B, &tm_hh, kb * 64, mt64 * 64, full + 8 * s);
            else bulk_g2s(sbase + s * P3_STAGE_B, g_o + ((size_t)mt64 * 12 + kb) * 8192, 8192, full + 8 * s);
            if (ph == 1 && kb == 5) {
              mbar_expect(bars + 8 * B_R3, 20480);
              tma3d(sbase + P3_R, &tm_xr, 0, mt64 * 64, nt4 * 5, bars + 8 * B_R3);
            }
            if (++s == NS) { s = 0; par ^= 1; }
          }
        }
        if (ph == 1) {
          tmap_prefetch(&tm_x1a);
          wait_flag(&g_sync[(C_X1 + mt) * 32], ep1 * 8);
          fence_async_global();
          mbar_wait(bars + 8 * B_GO4, 0);
#pragma unroll 1
          for (int it = 0; it < 20; it++) {
            const uint32_t fb = bars + 8 * (B_FULL4 + (it & 3));
            if (it >= P4_STAGES) mbar_wait(bars + 8 * (B_EMPTY4 + (it & 3)), ((it >> 2) - 1) & 1);
            mbar_expect(fb, 16384);
            tma2d(sbase + (it & 3) * P4_STAGE_B, &tm_x1a, (it < 10 ? it : it - 10) * 64, mt * 128, fb);
          }
        }
      }
    }
  }
}

typedef CUresult (*PFN_encodeTiled)(CUtensorMap*, CUtensorMapDataType, cuuint32_t, void*, const cuuint64_t*, const cuuint64_t*,
                                    const cuuint32_t*, const cuuint32_t*, CUtensorMapInterleave, CUtensorMapSwizzle,
                                    CUtensorMapL2promotion, CUtensorMapFloatOOBfill);
static PFN_encodeTiled g_encode = nullptr;

static CUtensorMap map2d(const void* p, uint64_t cols, uint64_t rows, uint32_t bc, uint32_t br, CUtensorMapSwizzle sw) {
  CUtensorMap m;
  cuuint64_t dims[2] = {cols, rows}, strides[1] = {cols * 2};
  cuuint32_t box[2] = {bc, br}, es[2] = {1, 1};
  g_encode(&m, CU_TENSOR_MAP_DATA_TYPE_BFLOAT16, 2, (void*)p, dims, strides, box, es, CU_TENSOR_MAP_INTERLEAVE_NONE, sw,
           CU_TENSOR_MAP_L2_PROMOTION_L2_256B, CU_TENSOR_MAP_FLOAT_OOB_FILL_NONE);
  return m;
}
static CUtensorMap map3d_g32(const void* p, uint64_t cols, uint64_t rows, uint32_t br, uint32_t ng = 5) {
  CUtensorMap m;
  cuuint64_t dims[3] = {32, rows, cols / 32}, strides[2] = {cols * 2, 64};
  cuuint32_t box[3] = {32, br, ng}, es[3] = {1, 1, 1};
  g_encode(&m, CU_TENSOR_MAP_DATA_TYPE_BFLOAT16, 3, (void*)p, dims, strides, box, es, CU_TENSOR_MAP_INTERLEAVE_NONE, CU_TENSOR_MAP_SWIZZLE_64B,
           CU_TENSOR_MAP_L2_PROMOTION_L2_256B, CU_TENSOR_MAP_FLOAT_OOB_FILL_NONE);
  return m;
}

extern "C" void kernel_launch(void* const* d_in, const int* in_sizes, int n_in, void* d_out, int out_size) {
  Ptrs P;
  P.x = (const bf16*)d_in[0];
  const bf16* wqkv = (const bf16*)d_in[1];
  P.wqkv = wqkv;
  P.wo = (const bf16*)d_in[2];
  P.wg = (const bf16*)d_in[4];
  P.wu = (const bf16*)d_in[5];
  P.wd = (const bf16*)d_in[6];
  P.c = (const bf16*)d_in[7];
  P.wmod = (const bf16*)d_in[8];
  bf16* out = (bf16*)d_out;

  if (!g_encode) {
    void* fn = nullptr;
    cudaDriverEntryPointQueryResult qr;
    cudaGetDriverEntryPoint("cuTensorMapEncodeTiled", &fn, cudaEnableDefault, &qr);
    g_encode = (PFN_encodeTiled)fn;
    cudaFuncSetAttribute(k_mega, cudaFuncAttributeMaxDynamicSharedMemorySize, MEGA_SMEM);
  }
  void *p_x1, *p_hh;
  cudaGetSymbolAddress(&p_x1, g_x1); cudaGetSymbolAddress(&p_hh, g_hh);

  const CUtensorMap tm_xa = map2d(P.x, DM, S_LEN, 64, 128, CU_TENSOR_MAP_SWIZZLE_128B);
  const CUtensorMap tm_wqkv = map2d(wqkv, 3 * DM, DM, 64, 64, CU_TENSOR_MAP_SWIZZLE_128B);
  const CUtensorMap tm_wo = map3d_g32(P.wo, DM, DM, 8);
  const CUtensorMap tm_xr = map3d_g32(P.x, DM, S_LEN, 64);
  const CUtensorMap tm_x1r = map3d_g32(p_x1, DM, S_LEN, 64);
  const CUtensorMap tm_x1a = map2d(p_x1, DM, S_LEN, 64, 128, CU_TENSOR_MAP_SWIZZLE_128B);
  const CUtensorMap tm_hh = map2d(p_hh, FF, S_LEN, 64, 64, CU_TENSOR_MAP_SWIZZLE_128B);
  const CUtensorMap tm_wd = map3d_g32(P.wd, DM, FF, 16);
  const CUtensorMap tm_out = map3d_g32(out, DM, S_LEN, 64);
  const CUtensorMap tm_wkv = map3d_g32(wqkv, 3 * DM, DM, 32);
  const CUtensorMap tm_hhs = map3d_g32(p_hh, FF, S_LEN, 64, 3);

  k_mega<<<132, 512, MEGA_SMEM, cudaStreamPerThread>>>(tm_xa, tm_wqkv, tm_wo, tm_xr, tm_x1r, tm_x1a, tm_hh, tm_wd, tm_out, tm_wkv, tm_hhs, P);
}
```
